```python
import torch

def _softmax(x, axis=-1):
    return torch.softmax(x, dim=axis)
def _gelu(x):
    return torch.nn.functional.gelu(x, approximate="tanh")
def _silu(x):
    return torch.nn.functional.silu(x)
def _sigmoid(x):
    return torch.sigmoid(x)
def _layernorm(x, axis=-1, eps=1e-5):
    m = x.mean(dim=axis, keepdim=True)
    v = x.var(dim=axis, keepdim=True, unbiased=False)
    return (x - m) / torch.sqrt(v + eps)
def _scatter_add(tgt, idx, src, axis=0):
    return tgt.clone().index_add_(axis, idx, src)
def _segment_sum(src, seg, n):
    out = torch.zeros((n,) + src.shape[1:], dtype=src.dtype)
    return out.index_add_(0, seg, src)
def _pad(x, pw):
    flat = tuple(v for pair in reversed(pw) for v in pair)
    return torch.nn.functional.pad(x, flat)

kernel_name = 'sequential_preLN__mha_block__mixer_token_mlp__prompt'

def setup_inputs():

    _w = (lambda a: (lambda t: t.to(torch.bfloat16) if t.is_floating_point() else t)(torch.as_tensor(a)))
    def _A_setup():
        B, S, D, H = 1, 2048, 1024, 32
        return {
            "x": _w((lambda *s: torch.randn(*s, dtype=torch.bfloat16) * 0.05)(B, S, D)),
            "wqkv": _w((lambda *s: torch.randn(*s, dtype=torch.bfloat16) * 0.05)(D, 3 * D)),
            "wo": _w((lambda *s: torch.randn(*s, dtype=torch.bfloat16) * 0.05)(D, D)),
        }
    _A_in = _A_setup()

    def _B_setup():
        B, S, D, F = 1, 2048, 1024, 3584
        return {
            "x": _w((lambda *s: torch.randn(*s, dtype=torch.bfloat16) * 0.05)(B, S, D)),
            "w1": _w((lambda *s: torch.randn(*s, dtype=torch.bfloat16) * 3.2)(S, F) * (S ** -0.5)),
            "b1": _w((lambda *s: torch.randn(*s, dtype=torch.bfloat16) * 3.2)(F) * 0.02),
            "w2": _w((lambda *s: torch.randn(*s, dtype=torch.bfloat16) * 0.4)(F, S) * (F ** -0.5)),
            "b2": _w((lambda *s: torch.randn(*s, dtype=torch.bfloat16) * 0.4)(S) * 0.02),
        }
    _B_in = _B_setup()

    return {
        "A_x": _A_in["x"],
        "A_wqkv": _A_in["wqkv"],
        "A_wo": _A_in["wo"],
        "B_x": _B_in["x"],
        "B_w1": _B_in["w1"],
        "B_b1": _B_in["b1"],
        "B_w2": _B_in["w2"],
        "B_b2": _B_in["b2"],
    }

def reference(A_x, A_wqkv, A_wo, B_x, B_w1, B_b1, B_w2, B_b2):
    def _A_ref(x, wqkv, wo):
        B, S, D = x.shape
        H = 32
        Dh = D // H
        qkv = (lambda x, *d: x.permute(*d))((x @ wqkv).reshape(B, S, 3, H, Dh), 2, 0, 3, 1, 4)
        q, k, v = qkv[0], qkv[1], qkv[2]
        scores = torch.einsum("bhqd,bhkd->bhqk", q, k) * (Dh ** -0.5)
        p = _softmax(scores, axis=-1)
        o = torch.einsum("bhqk,bhkd->bhqd", p, v)
        return (lambda x, *d: x.permute(*d))(o, 0, 2, 1, 3).reshape(B, S, D) @ wo

    def _B_ref(x, w1, b1, w2, b2):
        B, S, D = x.shape
        h = _layernorm(x, axis=-1)
        u = torch.einsum("bsd,sf->bdf", h, w1) + b1
        u = _gelu(u)
        y = torch.einsum("bdf,fs->bds", u, w2) + b2
        return (lambda x, *d: x.permute(*d))(y, 0, 2, 1)

    x = A_x
    h = x + _A_ref(_layernorm(x, axis=-1), A_wqkv, A_wo)
    h2 = h + _B_ref(_layernorm(h, axis=-1), B_w1, B_b1, B_w2, B_b2)
    return h2
```

```cpp
#include <cuda_runtime.h>
#include <cuda.h>
#include <cuda_bf16.h>
#include <stdint.h>
#include <stdio.h>
#include <string.h>

#define DEVINL __device__ __forceinline__
#define G1_SPLIT0 2
#define G1_SPLIT1 4
#define SPIN_NS 500
#define OP_RES_KB 15
#define G2_RES_KB 55
#define FILL_QKV 3
#define FILL_OP 3
#define FILL_G1 2
#define FILL_G2 4
#define ATT_FILL 1
#define ATT_Q2 2
#define ATT_WO 30
#define OP_PF 7
#define G1_PF 4
#define G1_PF0 26
#define QKV_TAIL 3
#define G1_TAILKB 4
#define PV_SPLIT 2
#define IDLE_NS 4000u
#define ATT_CREG 112
#define ATT_PREG 24
#define NPRE_OP 2
#define NPRE_G1 1
#define NPRE_G2 3
typedef __nv_bfloat16 bf16;

constexpr int S_LEN = 2048;
constexpr int D_MOD = 1024;
constexpr int NH = 32;
constexpr int DH = 32;
constexpr int F_DIM = 3584;
constexpr float LN_EPS = 1e-5f;
constexpr float QSCALE = 0.17677669529663687f * 1.4426950408889634f;

__device__ __align__(1024) bf16 g_qkv[S_LEN * 3 * D_MOD];
__device__ __align__(1024) float2 g_rowstat[2 * S_LEN];
__device__ __align__(1024) float g_colpart[24 * 3 * D_MOD];
__device__ __align__(1024) unsigned long long g_hpart[S_LEN * 8];
#define CNT_PAD 32
__device__ __align__(128) unsigned int g_cnt_row[8 * CNT_PAD], g_cnt_col[16 * CNT_PAD];
constexpr unsigned long long HP_EMPTY = 0ull;
__device__ __align__(1024) float g_stats[96 * 128];
__device__ __align__(1024) bf16 g_o[S_LEN * D_MOD];
__device__ __align__(1024) float2 g_rowmk[S_LEN];
__device__ __align__(1024) bf16 g_hn[S_LEN * D_MOD];
__device__ __align__(1024) bf16 g_u[D_MOD * F_DIM];

DEVINL uint32_t smem_u32(const void* p) { return (uint32_t)__cvta_generic_to_shared(p); }
DEVINL void mbar_init(uint32_t bar, uint32_t count) { asm volatile("mbarrier.init.shared::cta.b64 [%0], %1;" :: "r"(bar), "r"(count) : "memory"); }
DEVINL void mbar_expect_tx(uint32_t bar, uint32_t bytes) { asm volatile("mbarrier.arrive.expect_tx.shared::cta.b64 _, [%0], %1;" :: "r"(bar), "r"(bytes) : "memory"); }
DEVINL void mbar_arrive(uint32_t bar) { asm volatile("mbarrier.arrive.shared::cta.b64 _, [%0];" :: "r"(bar) : "memory"); }
DEVINL void mbar_arrive_cluster(uint32_t bar, uint32_t cta) {
  asm volatile("{\n.reg .b32 ra;\nmapa.shared::cluster.u32 ra, %0, %1;\nmbarrier.arrive.shared::cluster.b64 _, [ra];\n}" :: "r"(bar), "r"(cta) : "memory");
}
DEVINL void mbar_wait(uint32_t bar, uint32_t parity) {
  asm volatile("{\n.reg .pred P1;\n.reg .pred P2;\n.reg .u32 cnt;\nmov.u32 cnt, 0;\n"
    "LAB_WAIT:\n"
    "mbarrier.try_wait.parity.shared::cta.b64 P1, [%0], %1;\n"
    "@P1 bra DONE;\n"
    "add.u32 cnt, cnt, 1;\n"
    "setp.lt.u32 P2, cnt, 4194304;\n"
    "@P2 bra LAB_WAIT;\n"
    "trap;\n"
    "DONE:\n}" :: "r"(bar), "r"(parity) : "memory");
}
DEVINL void mbar_wait_idle(uint32_t bar, uint32_t parity) {
  asm volatile("{\n.reg .pred P1;\n.reg .pred P2;\n.reg .u32 cnt;\nmov.u32 cnt, 0;\n"
    "LAB_WAIT:\n"
    "mbarrier.try_wait.parity.shared::cta.b64 P1, [%0], %1, %2;\n"
    "@P1 bra DONE;\n"
    "add.u32 cnt, cnt, 1;\n"
    "setp.lt.u32 P2, cnt, 262144;\n"
    "@P2 bra LAB_WAIT;\n"
    "trap;\n"
    "DONE:\n}" :: "r"(bar), "r"(parity), "r"(IDLE_NS) : "memory");
}
DEVINL void fence_barrier_init() { asm volatile("fence.mbarrier_init.release.cluster;" ::: "memory"); }
DEVINL void fence_proxy_async() { asm volatile("fence.proxy.async.shared::cta;" ::: "memory"); }
DEVINL void cluster_arrive_relaxed() { asm volatile("barrier.cluster.arrive.relaxed.aligned;" ::: "memory"); }
DEVINL void cluster_wait() { asm volatile("barrier.cluster.wait.acquire.aligned;" ::: "memory"); }
DEVINL uint32_t cluster_rank() { uint32_t r; asm volatile("mov.u32 %0, %%cluster_ctarank;" : "=r"(r)); return r; }
DEVINL void bulk_load(uint32_t dst, const void* src, uint32_t bytes, uint32_t bar) {
  asm volatile("cp.async.bulk.shared::cluster.global.mbarrier::complete_tx::bytes [%0], [%1], %2, [%3];" :: "r"(dst), "l"(src), "r"(bytes), "r"(bar) : "memory");
}
DEVINL void bulk_store(void* dst, uint32_t src, uint32_t bytes) {
  asm volatile("cp.async.bulk.global.shared::cta.bulk_group [%0], [%1], %2;" :: "l"(dst), "r"(src), "r"(bytes) : "memory");
}
DEVINL void prefetch_tmap(const CUtensorMap* m) { asm volatile("prefetch.tensormap [%0];" :: "l"(m) : "memory"); }
DEVINL void named_bar_sync(int id, int n) { asm volatile("bar.sync %0, %1;" :: "r"(id), "r"(n) : "memory"); }
DEVINL void named_bar_arrive(int id, int n) { asm volatile("bar.arrive %0, %1;" :: "r"(id), "r"(n) : "memory"); }
DEVINL void pdl_wait() { asm volatile("griddepcontrol.wait;" ::: "memory"); }
DEVINL void pdl_launch() { asm volatile("griddepcontrol.launch_dependents;" ::: "memory"); }

DEVINL void tma_load_2d(uint32_t dst, const CUtensorMap* m, uint32_t bar, int c0, int c1) {
  asm volatile("cp.async.bulk.tensor.2d.shared::cluster.global.mbarrier::complete_tx::bytes [%0], [%1, {%3, %4}], [%2];"
    :: "r"(dst), "l"(m), "r"(bar), "r"(c0), "r"(c1) : "memory");
}
DEVINL void tma_load_2d_mc(uint32_t dst, const CUtensorMap* m, uint32_t bar, int c0, int c1, uint16_t mask) {
  asm volatile("cp.async.bulk.tensor.2d.shared::cluster.global.mbarrier::complete_tx::bytes.multicast::cluster [%0], [%1, {%3, %4}], [%2], %5;"
    :: "r"(dst), "l"(m), "r"(bar), "r"(c0), "r"(c1), "h"(mask) : "memory");
}
DEVINL void tma_load_3d(uint32_t dst, const CUtensorMap* m, uint32_t bar, int c0, int c1, int c2) {
  asm volatile("cp.async.bulk.tensor.3d.shared::cluster.global.mbarrier::complete_tx::bytes [%0], [%1, {%3, %4, %5}], [%2];"
    :: "r"(dst), "l"(m), "r"(bar), "r"(c0), "r"(c1), "r"(c2) : "memory");
}
DEVINL void tma_load_3d_mc(uint32_t dst, const CUtensorMap* m, uint32_t bar, int c0, int c1, int c2, uint16_t mask) {
  asm volatile("cp.async.bulk.tensor.3d.shared::cluster.global.mbarrier::complete_tx::bytes.multicast::cluster [%0], [%1, {%3, %4, %5}], [%2], %6;"
    :: "r"(dst), "l"(m), "r"(bar), "r"(c0), "r"(c1), "r"(c2), "h"(mask) : "memory");
}
DEVINL void tma_store_2d(const CUtensorMap* m, uint32_t src, int c0, int c1) {
  asm volatile("cp.async.bulk.tensor.2d.global.shared::cta.bulk_group [%0, {%2, %3}], [%1];"
    :: "l"(m), "r"(src), "r"(c0), "r"(c1) : "memory");
}
DEVINL void tma_store_commit() { asm volatile("cp.async.bulk.commit_group;" ::: "memory"); }
DEVINL void tma_store_wait_read() { asm volatile("cp.async.bulk.wait_group.read 0;" ::: "memory"); }

DEVINL void wg_fence() { asm volatile("wgmma.fence.sync.aligned;" ::: "memory"); }
DEVINL void wg_commit() { asm volatile("wgmma.commit_group.sync.aligned;" ::: "memory"); }
template<int N> DEVINL void wg_wait() { asm volatile("wgmma.wait_group.sync.aligned %0;" :: "n"(N) : "memory"); }
template<int R> DEVINL void reg_alloc() { asm volatile("setmaxnreg.inc.sync.aligned.u32 %0;" :: "n"(R)); }
template<int R> DEVINL void reg_dealloc() { asm volatile("setmaxnreg.dec.sync.aligned.u32 %0;" :: "n"(R)); }
template<int N> DEVINL void fence_regs(float (&d)[N]) {
#pragma unroll
  for (int i = 0; i < N; i++) asm volatile("" : "+f"(d[i]) :: "memory");
}
template<int N> DEVINL void fence_u32(uint32_t (&d)[N]) {
#pragma unroll
  for (int i = 0; i < N; i++) asm volatile("" : "+r"(d[i]) :: "memory");
}
DEVINL uint64_t make_desc(uint32_t saddr, uint32_t lbo, uint32_t sbo, uint32_t swz) {
  uint64_t d = 0;
  d |= (uint64_t)((saddr & 0x3FFFF) >> 4);
  d |= (uint64_t)((lbo & 0x3FFFF) >> 4) << 16;
  d |= (uint64_t)((sbo & 0x3FFFF) >> 4) << 32;
  d |= (uint64_t)swz << 62;
  return d;
}
DEVINL uint32_t pack_bf16(float lo, float hi) { uint32_t r; asm("cvt.rn.bf16x2.f32 %0, %1, %2;" : "=r"(r) : "f"(hi), "f"(lo)); return r; }
DEVINL float bf_lo(uint32_t v) { return __uint_as_float(v << 16); }
DEVINL float bf_hi(uint32_t v) { return __uint_as_float(v & 0xFFFF0000u); }
DEVINL void stmatrix_x4(uint32_t addr, uint32_t r0, uint32_t r1, uint32_t r2, uint32_t r3) {
  asm volatile("stmatrix.sync.aligned.m8n8.x4.shared.b16 [%0], {%1, %2, %3, %4};" :: "r"(addr), "r"(r0), "r"(r1), "r"(r2), "r"(r3));
}
DEVINL void ldmatrix_x4(uint32_t addr, uint32_t& r0, uint32_t& r1, uint32_t& r2, uint32_t& r3) {
  asm volatile("ldmatrix.sync.aligned.m8n8.x4.shared.b16 {%0, %1, %2, %3}, [%4];" : "=r"(r0), "=r"(r1), "=r"(r2), "=r"(r3) : "r"(addr) : "memory");
}
DEVINL uint32_t ld_acquire(const unsigned int* p) { uint32_t v; asm volatile("ld.acquire.gpu.global.u32 %0, [%1];" : "=r"(v) : "l"(p) : "memory"); return v; }
DEVINL void red_release_add(unsigned int* p, uint32_t v) { asm volatile("red.release.gpu.global.add.u32 [%0], %1;" :: "l"(p), "r"(v) : "memory"); }
DEVINL void spin_until(const unsigned int* p, uint32_t target) {
  uint32_t n = 0;
  while (ld_acquire(p) < target) { if (SPIN_NS > 0) __nanosleep(SPIN_NS); if (++n > (1u << 22)) __trap(); }
}
DEVINL void st_relaxed_u64(unsigned long long* p, unsigned long long v) { asm volatile("st.relaxed.gpu.global.u64 [%0], %1;" :: "l"(p), "l"(v) : "memory"); }
DEVINL unsigned long long ld_relaxed_u64(const unsigned long long* p) { unsigned long long v; asm volatile("ld.relaxed.gpu.global.u64 %0, [%1];" : "=l"(v) : "l"(p) : "memory"); return v; }
DEVINL void l2_prefetch(const void* p, uint32_t bytes) { asm volatile("cp.async.bulk.prefetch.L2.global [%0], %1;" :: "l"(p), "r"(bytes) : "memory"); }
DEVINL uint32_t redux_max_u32(uint32_t v) { uint32_t r; asm volatile("redux.sync.max.u32 %0, %1, 0xffffffff;" : "=r"(r) : "r"(v)); return r; }
DEVINL float ex2_mufu(float x) { float y; asm("ex2.approx.ftz.f32 %0, %1;" : "=f"(y) : "f"(x)); return y; }
DEVINL float tanh_mufu(float x) { float y; asm("tanh.approx.f32 %0, %1;" : "=f"(y) : "f"(x)); return y; }

template<int TA, int TB> __device__ __forceinline__ void wgmma_n128_ss(float (&d)[64], uint64_t da, uint64_t db, int sd) {
  asm volatile("{\n.reg .pred p;\n"
    "setp.ne.b32 p, %66, 0;\n"
    "wgmma.mma_async.sync.aligned.m64n128k16.f32.bf16.bf16 "
    "{%0, %1, %2, %3, %4, %5, %6, %7, %8, %9, %10, %11, %12, %13, %14, %15, "
    "%16, %17, %18, %19, %20, %21, %22, %23, %24, %25, %26, %27, %28, %29, %30, %31, "
    "%32, %33, %34, %35, %36, %37, %38, %39, %40, %41, %42, %43, %44, %45, %46, %47, "
    "%48, %49, %50, %51, %52, %53, %54, %55, %56, %57, %58, %59, %60, %61, %62, %63}, "
    "%64, %65, p, 1, 1, %67, %68;\n}\n"
    : "+f"(d[0]), "+f"(d[1]), "+f"(d[2]), "+f"(d[3]), "+f"(d[4]), "+f"(d[5]), "+f"(d[6]), "+f"(d[7]),
      "+f"(d[8]), "+f"(d[9]), "+f"(d[10]), "+f"(d[11]), "+f"(d[12]), "+f"(d[13]), "+f"(d[14]), "+f"(d[15]),
      "+f"(d[16]), "+f"(d[17]), "+f"(d[18]), "+f"(d[19]), "+f"(d[20]), "+f"(d[21]), "+f"(d[22]), "+f"(d[23]),
      "+f"(d[24]), "+f"(d[25]), "+f"(d[26]), "+f"(d[27]), "+f"(d[28]), "+f"(d[29]), "+f"(d[30]), "+f"(d[31]),
      "+f"(d[32]), "+f"(d[33]), "+f"(d[34]), "+f"(d[35]), "+f"(d[36]), "+f"(d[37]), "+f"(d[38]), "+f"(d[39]),
      "+f"(d[40]), "+f"(d[41]), "+f"(d[42]), "+f"(d[43]), "+f"(d[44]), "+f"(d[45]), "+f"(d[46]), "+f"(d[47]),
      "+f"(d[48]), "+f"(d[49]), "+f"(d[50]), "+f"(d[51]), "+f"(d[52]), "+f"(d[53]), "+f"(d[54]), "+f"(d[55]),
      "+f"(d[56]), "+f"(d[57]), "+f"(d[58]), "+f"(d[59]), "+f"(d[60]), "+f"(d[61]), "+f"(d[62]), "+f"(d[63])
    : "l"(da), "l"(db), "r"(sd), "n"(TA), "n"(TB));
}

template<int TA, int TB> __device__ __forceinline__ void wgmma_n192_ss(float (&d)[96], uint64_t da, uint64_t db, int sd) {
  asm volatile("{\n.reg .pred p;\n"
    "setp.ne.b32 p, %98, 0;\n"
    "wgmma.mma_async.sync.aligned.m64n192k16.f32.bf16.bf16 "
    "{%0, %1, %2, %3, %4, %5, %6, %7, %8, %9, %10, %11, %12, %13, %14, %15, "
    "%16, %17, %18, %19, %20, %21, %22, %23, %24, %25, %26, %27, %28, %29, %30, %31, "
    "%32, %33, %34, %35, %36, %37, %38, %39, %40, %41, %42, %43, %44, %45, %46, %47, "
    "%48, %49, %50, %51, %52, %53, %54, %55, %56, %57, %58, %59, %60, %61, %62, %63, "
    "%64, %65, %66, %67, %68, %69, %70, %71, %72, %73, %74, %75, %76, %77, %78, %79, "
    "%80, %81, %82, %83, %84, %85, %86, %87, %88, %89, %90, %91, %92, %93, %94, %95}, "
    "%96, %97, p, 1, 1, %99, %100;\n}\n"
    : "+f"(d[0]), "+f"(d[1]), "+f"(d[2]), "+f"(d[3]), "+f"(d[4]), "+f"(d[5]), "+f"(d[6]), "+f"(d[7]),
      "+f"(d[8]), "+f"(d[9]), "+f"(d[10]), "+f"(d[11]), "+f"(d[12]), "+f"(d[13]), "+f"(d[14]), "+f"(d[15]),
      "+f"(d[16]), "+f"(d[17]), "+f"(d[18]), "+f"(d[19]), "+f"(d[20]), "+f"(d[21]), "+f"(d[22]), "+f"(d[23]),
      "+f"(d[24]), "+f"(d[25]), "+f"(d[26]), "+f"(d[27]), "+f"(d[28]), "+f"(d[29]), "+f"(d[30]), "+f"(d[31]),
      "+f"(d[32]), "+f"(d[33]), "+f"(d[34]), "+f"(d[35]), "+f"(d[36]), "+f"(d[37]), "+f"(d[38]), "+f"(d[39]),
      "+f"(d[40]), "+f"(d[41]), "+f"(d[42]), "+f"(d[43]), "+f"(d[44]), "+f"(d[45]), "+f"(d[46]), "+f"(d[47]),
      "+f"(d[48]), "+f"(d[49]), "+f"(d[50]), "+f"(d[51]), "+f"(d[52]), "+f"(d[53]), "+f"(d[54]), "+f"(d[55]),
      "+f"(d[56]), "+f"(d[57]), "+f"(d[58]), "+f"(d[59]), "+f"(d[60]), "+f"(d[61]), "+f"(d[62]), "+f"(d[63]),
      "+f"(d[64]), "+f"(d[65]), "+f"(d[66]), "+f"(d[67]), "+f"(d[68]), "+f"(d[69]), "+f"(d[70]), "+f"(d[71]),
      "+f"(d[72]), "+f"(d[73]), "+f"(d[74]), "+f"(d[75]), "+f"(d[76]), "+f"(d[77]), "+f"(d[78]), "+f"(d[79]),
      "+f"(d[80]), "+f"(d[81]), "+f"(d[82]), "+f"(d[83]), "+f"(d[84]), "+f"(d[85]), "+f"(d[86]), "+f"(d[87]),
      "+f"(d[88]), "+f"(d[89]), "+f"(d[90]), "+f"(d[91]), "+f"(d[92]), "+f"(d[93]), "+f"(d[94]), "+f"(d[95])
    : "l"(da), "l"(db), "r"(sd), "n"(TA), "n"(TB));
}

template<int TA, int TB> __device__ __forceinline__ void wgmma_n224_ss(float (&d)[112], uint64_t da, uint64_t db, int sd) {
  asm volatile("{\n.reg .pred p;\n"
    "setp.ne.b32 p, %114, 0;\n"
    "wgmma.mma_async.sync.aligned.m64n224k16.f32.bf16.bf16 "
    "{%0, %1, %2, %3, %4, %5, %6, %7, %8, %9, %10, %11, %12, %13, %14, %15, "
    "%16, %17, %18, %19, %20, %21, %22, %23, %24, %25, %26, %27, %28, %29, %30, %31, "
    "%32, %33, %34, %35, %36, %37, %38, %39, %40, %41, %42, %43, %44, %45, %46, %47, "
    "%48, %49, %50, %51, %52, %53, %54, %55, %56, %57, %58, %59, %60, %61, %62, %63, "
    "%64, %65, %66, %67, %68, %69, %70, %71, %72, %73, %74, %75, %76, %77, %78, %79, "
    "%80, %81, %82, %83, %84, %85, %86, %87, %88, %89, %90, %91, %92, %93, %94, %95, "
    "%96, %97, %98, %99, %100, %101, %102, %103, %104, %105, %106, %107, %108, %109, %110, %111}, "
    "%112, %113, p, 1, 1, %115, %116;\n}\n"
    : "+f"(d[0]), "+f"(d[1]), "+f"(d[2]), "+f"(d[3]), "+f"(d[4]), "+f"(d[5]), "+f"(d[6]), "+f"(d[7]),
      "+f"(d[8]), "+f"(d[9]), "+f"(d[10]), "+f"(d[11]), "+f"(d[12]), "+f"(d[13]), "+f"(d[14]), "+f"(d[15]),
      "+f"(d[16]), "+f"(d[17]), "+f"(d[18]), "+f"(d[19]), "+f"(d[20]), "+f"(d[21]), "+f"(d[22]), "+f"(d[23]),
      "+f"(d[24]), "+f"(d[25]), "+f"(d[26]), "+f"(d[27]), "+f"(d[28]), "+f"(d[29]), "+f"(d[30]), "+f"(d[31]),
      "+f"(d[32]), "+f"(d[33]), "+f"(d[34]), "+f"(d[35]), "+f"(d[36]), "+f"(d[37]), "+f"(d[38]), "+f"(d[39]),
      "+f"(d[40]), "+f"(d[41]), "+f"(d[42]), "+f"(d[43]), "+f"(d[44]), "+f"(d[45]), "+f"(d[46]), "+f"(d[47]),
      "+f"(d[48]), "+f"(d[49]), "+f"(d[50]), "+f"(d[51]), "+f"(d[52]), "+f"(d[53]), "+f"(d[54]), "+f"(d[55]),
      "+f"(d[56]), "+f"(d[57]), "+f"(d[58]), "+f"(d[59]), "+f"(d[60]), "+f"(d[61]), "+f"(d[62]), "+f"(d[63]),
      "+f"(d[64]), "+f"(d[65]), "+f"(d[66]), "+f"(d[67]), "+f"(d[68]), "+f"(d[69]), "+f"(d[70]), "+f"(d[71]),
      "+f"(d[72]), "+f"(d[73]), "+f"(d[74]), "+f"(d[75]), "+f"(d[76]), "+f"(d[77]), "+f"(d[78]), "+f"(d[79]),
      "+f"(d[80]), "+f"(d[81]), "+f"(d[82]), "+f"(d[83]), "+f"(d[84]), "+f"(d[85]), "+f"(d[86]), "+f"(d[87]),
      "+f"(d[88]), "+f"(d[89]), "+f"(d[90]), "+f"(d[91]), "+f"(d[92]), "+f"(d[93]), "+f"(d[94]), "+f"(d[95]),
      "+f"(d[96]), "+f"(d[97]), "+f"(d[98]), "+f"(d[99]), "+f"(d[100]), "+f"(d[101]), "+f"(d[102]), "+f"(d[103]),
      "+f"(d[104]), "+f"(d[105]), "+f"(d[106]), "+f"(d[107]), "+f"(d[108]), "+f"(d[109]), "+f"(d[110]), "+f"(d[111])
    : "l"(da), "l"(db), "r"(sd), "n"(TA), "n"(TB));
}

template<int TA, int TB> __device__ __forceinline__ void wgmma_n96_ss(float (&d)[48], uint64_t da, uint64_t db, int sd) {
  asm volatile("{\n.reg .pred p;\n"
    "setp.ne.b32 p, %50, 0;\n"
    "wgmma.mma_async.sync.aligned.m64n96k16.f32.bf16.bf16 "
    "{%0, %1, %2, %3, %4, %5, %6, %7, %8, %9, %10, %11, %12, %13, %14, %15, "
    "%16, %17, %18, %19, %20, %21, %22, %23, %24, %25, %26, %27, %28, %29, %30, %31, "
    "%32, %33, %34, %35, %36, %37, %38, %39, %40, %41, %42, %43, %44, %45, %46, %47}, "
    "%48, %49, p, 1, 1, %51, %52;\n}\n"
    : "+f"(d[0]), "+f"(d[1]), "+f"(d[2]), "+f"(d[3]), "+f"(d[4]), "+f"(d[5]), "+f"(d[6]), "+f"(d[7]),
      "+f"(d[8]), "+f"(d[9]), "+f"(d[10]), "+f"(d[11]), "+f"(d[12]), "+f"(d[13]), "+f"(d[14]), "+f"(d[15]),
      "+f"(d[16]), "+f"(d[17]), "+f"(d[18]), "+f"(d[19]), "+f"(d[20]), "+f"(d[21]), "+f"(d[22]), "+f"(d[23]),
      "+f"(d[24]), "+f"(d[25]), "+f"(d[26]), "+f"(d[27]), "+f"(d[28]), "+f"(d[29]), "+f"(d[30]), "+f"(d[31]),
      "+f"(d[32]), "+f"(d[33]), "+f"(d[34]), "+f"(d[35]), "+f"(d[36]), "+f"(d[37]), "+f"(d[38]), "+f"(d[39]),
      "+f"(d[40]), "+f"(d[41]), "+f"(d[42]), "+f"(d[43]), "+f"(d[44]), "+f"(d[45]), "+f"(d[46]), "+f"(d[47])
    : "l"(da), "l"(db), "r"(sd), "n"(TA), "n"(TB));
}

template<int TB> __device__ __forceinline__ void wgmma_n64_rs(float (&d)[32], uint32_t a0, uint32_t a1, uint32_t a2, uint32_t a3, uint64_t db, int sd) {
  asm volatile("{\n.reg .pred p;\n"
    "setp.ne.b32 p, %37, 0;\n"
    "wgmma.mma_async.sync.aligned.m64n64k16.f32.bf16.bf16 "
    "{%0, %1, %2, %3, %4, %5, %6, %7, %8, %9, %10, %11, %12, %13, %14, %15, "
    "%16, %17, %18, %19, %20, %21, %22, %23, %24, %25, %26, %27, %28, %29, %30, %31}, "
    "{%32, %33, %34, %35}, %36, p, 1, 1, %38;\n}\n"
    : "+f"(d[0]), "+f"(d[1]), "+f"(d[2]), "+f"(d[3]), "+f"(d[4]), "+f"(d[5]), "+f"(d[6]), "+f"(d[7]),
      "+f"(d[8]), "+f"(d[9]), "+f"(d[10]), "+f"(d[11]), "+f"(d[12]), "+f"(d[13]), "+f"(d[14]), "+f"(d[15]),
      "+f"(d[16]), "+f"(d[17]), "+f"(d[18]), "+f"(d[19]), "+f"(d[20]), "+f"(d[21]), "+f"(d[22]), "+f"(d[23]),
      "+f"(d[24]), "+f"(d[25]), "+f"(d[26]), "+f"(d[27]), "+f"(d[28]), "+f"(d[29]), "+f"(d[30]), "+f"(d[31])
    : "r"(a0), "r"(a1), "r"(a2), "r"(a3), "l"(db), "r"(sd), "n"(TB));
}

template<int TB> __device__ __forceinline__ void wgmma_n64_rsz(float (&d)[32], uint32_t a0, uint32_t a1, uint32_t a2, uint32_t a3, uint64_t db, int sd) {
  asm volatile("{\n.reg .pred p;\n"
    "setp.ne.b32 p, 0, 0;\n"
    "wgmma.mma_async.sync.aligned.m64n64k16.f32.bf16.bf16 "
    "{%0, %1, %2, %3, %4, %5, %6, %7, %8, %9, %10, %11, %12, %13, %14, %15, "
    "%16, %17, %18, %19, %20, %21, %22, %23, %24, %25, %26, %27, %28, %29, %30, %31}, "
    "{%32, %33, %34, %35}, %36, p, 1, 1, %38;\n}\n"
    : "=f"(d[0]), "=f"(d[1]), "=f"(d[2]), "=f"(d[3]), "=f"(d[4]), "=f"(d[5]), "=f"(d[6]), "=f"(d[7]),
      "=f"(d[8]), "=f"(d[9]), "=f"(d[10]), "=f"(d[11]), "=f"(d[12]), "=f"(d[13]), "=f"(d[14]), "=f"(d[15]),
      "=f"(d[16]), "=f"(d[17]), "=f"(d[18]), "=f"(d[19]), "=f"(d[20]), "=f"(d[21]), "=f"(d[22]), "=f"(d[23]),
      "=f"(d[24]), "=f"(d[25]), "=f"(d[26]), "=f"(d[27]), "=f"(d[28]), "=f"(d[29]), "=f"(d[30]), "=f"(d[31])
    : "r"(a0), "r"(a1), "r"(a2), "r"(a3), "l"(db), "r"(sd), "n"(TB));
}

template<int TB> __device__ __forceinline__ void wgmma_n40_rs(float (&d)[20], uint32_t a0, uint32_t a1, uint32_t a2, uint32_t a3, uint64_t db, int sd) {
  asm volatile("{\n.reg .pred p;\n"
    "setp.ne.b32 p, %25, 0;\n"
    "wgmma.mma_async.sync.aligned.m64n40k16.f32.bf16.bf16 "
    "{%0, %1, %2, %3, %4, %5, %6, %7, %8, %9, %10, %11, %12, %13, %14, %15, "
    "%16, %17, %18, %19}, "
    "{%20, %21, %22, %23}, %24, p, 1, 1, %26;\n}\n"
    : "+f"(d[0]), "+f"(d[1]), "+f"(d[2]), "+f"(d[3]), "+f"(d[4]), "+f"(d[5]), "+f"(d[6]), "+f"(d[7]),
      "+f"(d[8]), "+f"(d[9]), "+f"(d[10]), "+f"(d[11]), "+f"(d[12]), "+f"(d[13]), "+f"(d[14]), "+f"(d[15]),
      "+f"(d[16]), "+f"(d[17]), "+f"(d[18]), "+f"(d[19])
    : "r"(a0), "r"(a1), "r"(a2), "r"(a3), "l"(db), "r"(sd), "n"(TB));
}

template<int N> struct WG;
template<> struct WG<128> { template<int TA,int TB> static DEVINL void mma(float (&d)[64], uint64_t a, uint64_t b, int sd) { wgmma_n128_ss<TA,TB>(d,a,b,sd);} };
template<> struct WG<192> { template<int TA,int TB> static DEVINL void mma(float (&d)[96], uint64_t a, uint64_t b, int sd) { wgmma_n192_ss<TA,TB>(d,a,b,sd);} };
template<> struct WG<224> { template<int TA,int TB> static DEVINL void mma(float (&d)[112], uint64_t a, uint64_t b, int sd) { wgmma_n224_ss<TA,TB>(d,a,b,sd);} };

enum { EPI_QKV = 0, EPI_OP = 1, EPI_G1 = 2, EPI_G2 = 3 };

struct alignas(64) GemmParams {
  CUtensorMap tmA, tmB, tmC, tmR, tmC2;
  const bf16* bias;
  const bf16* x;
  const bf16* w;
};

template<int EPI_, int MREP_, int BN_, int A_MN_, int B_MN_, int B_RB_, int STAGES_, int CM_, int CN_, int MT_, int NT_, int KB_, int CREG_, int PREG_>
struct Cfg {
  static constexpr int EPI = EPI_, MREP = MREP_, BM = 128 * MREP_, BN = BN_, A_MN = A_MN_, B_MN = B_MN_, B_RB = B_RB_, STAGES = STAGES_;
  static constexpr int CM = CM_, CN = CN_, MT = MT_, NT = NT_, KB = KB_, CREG = CREG_, PREG = PREG_;
  static constexpr int A_BYTES = BM * 128, B_BYTES = BN * 128, STAGE_BYTES = A_BYTES + B_BYTES;
  static constexpr int RES_BYTES = (EPI_ == EPI_OP || EPI_ == EPI_G2) ? BM * BN * 2 : 0;
  static constexpr int AUX_BYTES = EPI_ == EPI_QKV ? 256 + 768 : 1280;
  static constexpr int SMEM = STAGES * STAGE_BYTES + RES_BYTES + AUX_BYTES + 1024;
  static constexpr int A_RS = 64 / CN, B_RS = 64 / CM, A_CH = BM / 64, B_CH = BN * 2 / B_RB;
  static constexpr int GRID = MT * NT;
};

template<class C>
__global__ void __launch_bounds__(384, 1) gemm_kernel(const __grid_constant__ GemmParams p) {
  extern __shared__ uint8_t smem_raw[];
  const uint32_t sbase = (smem_u32(smem_raw) + 1023) & ~1023u;
  const uint32_t sres = sbase + C::STAGES * C::STAGE_BYTES;
  const uint32_t saux = sres + C::RES_BYTES;
  const uint32_t bar_full = saux, bar_empty = saux + 64, bar_res = saux + 128, sbias = saux + 256;
  const int warp = threadIdx.x >> 5, lane = threadIdx.x & 31, wg = threadIdx.x >> 7;
  constexpr int CS = C::CM * C::CN;
  const int r = CS > 1 ? (int)cluster_rank() : 0;
  const int rm = r % C::CM, rn = r / C::CM;
  const int cid = blockIdx.x / CS;
  const int mt = (cid % (C::MT / C::CM)) * C::CM + rm;
  const int nt = (cid / (C::MT / C::CM)) * C::CN + rn;

  constexpr bool EARLY = (C::EPI == EPI_QKV) && CS == 1;
  const int koff = C::EPI == EPI_QKV ? ((mt + nt) & 1) * 8 : 0;
  if (threadIdx.x == 256) {
    prefetch_tmap(&p.tmA); prefetch_tmap(&p.tmB);
    for (int s = 0; s < C::STAGES; s++) { mbar_init(bar_full + 8 * s, 1); mbar_init(bar_empty + 8 * s, (C::EPI == EPI_QKV ? 5 : 2) * (C::CM + C::CN - 1)); }
    mbar_init(bar_res, C::EPI == EPI_QKV ? 65 : 1);
    if constexpr (!EARLY) {
#pragma unroll
      for (int s = 0; s < C::STAGES; s++) mbar_expect_tx(bar_full + 8 * s, C::STAGE_BYTES);
    }
    fence_barrier_init();
    if constexpr (EARLY) {
      fence_proxy_async();
#pragma unroll
      for (int s = 0; s < (FILL_QKV < C::STAGES ? FILL_QKV : C::STAGES); s++) {
        const uint32_t dst = sbase + s * C::STAGE_BYTES, fb = bar_full + 8 * s;
        mbar_expect_tx(fb, C::STAGE_BYTES);
        tma_load_2d(dst, &p.tmA, fb, (s + koff) * 64, mt * C::BM);
        tma_load_3d(dst + C::A_BYTES, &p.tmB, fb, 0, (s + koff) * 64, nt * C::B_CH);
      }
    }
  }
  uint16_t maskA = 0, maskB = 0;
  for (int j = 0; j < C::CN; j++) maskA |= 1 << (rm + j * C::CM);
  for (int j = 0; j < C::CM; j++) maskB |= 1 << (rn * C::CM + j);
  auto loadA = [&](int s, int kb) {
    const uint32_t dst = sbase + s * C::STAGE_BYTES + rn * (C::A_BYTES / C::CN), fb = bar_full + 8 * s;
    const int k0 = C::EPI == EPI_QKV ? ((kb + koff) & 15) * 64 : kb * 64;
    if (C::A_MN) {
      if (C::CN > 1) tma_load_3d_mc(dst, &p.tmA, fb, 0, k0 + rn * C::A_RS, mt * C::A_CH, maskA);
      else tma_load_3d(dst, &p.tmA, fb, 0, k0, mt * C::A_CH);
    } else {
      if (C::CN > 1) tma_load_2d_mc(dst, &p.tmA, fb, k0, mt * C::BM + rn * (C::BM / C::CN), maskA);
      else tma_load_2d(dst, &p.tmA, fb, k0, mt * C::BM);
    }
  };
  auto loadB = [&](int s, int kb) {
    const uint32_t dst = sbase + s * C::STAGE_BYTES + C::A_BYTES + rm * (C::B_BYTES / C::CM), fb = bar_full + 8 * s;
    const int k0 = C::EPI == EPI_QKV ? ((kb + koff) & 15) * 64 : kb * 64;
    if (C::B_MN) {
      if (C::CM > 1) tma_load_3d_mc(dst, &p.tmB, fb, 0, k0 + rm * C::B_RS, nt * C::B_CH, maskB);
      else tma_load_3d(dst, &p.tmB, fb, 0, k0, nt * C::B_CH);
    } else {
      if (C::CM > 1) tma_load_2d_mc(dst, &p.tmB, fb, k0, nt * C::BN + rm * (C::BN / C::CM), maskB);
      else tma_load_2d(dst, &p.tmB, fb, k0, nt * C::BN);
    }
  };
  constexpr bool W_IS_A = (C::EPI == EPI_G2);
  constexpr int NPRE = C::EPI == EPI_QKV ? 0 : C::EPI == EPI_OP ? NPRE_OP : C::EPI == EPI_G1 ? NPRE_G1 : NPRE_G2;
  constexpr int FILLD = C::EPI == EPI_OP ? FILL_OP : C::EPI == EPI_G1 ? FILL_G1 : FILL_G2;
  __syncthreads();
  if (CS > 1) { cluster_arrive_relaxed(); cluster_wait(); }
  pdl_launch();

  if (wg == 2) {
    reg_dealloc<C::PREG>();
    if constexpr (C::EPI == EPI_QKV) {
      int stgt = -1;
      if (lane < C::CN) stgt = rm + lane * C::CM;
      else if (lane < C::CN + C::CM - 1) { int j = lane - C::CN; if (j >= rm) j++; stgt = rn * C::CM + j; }
      if (warp == 9 || warp == 11) {
        const int r = (nt >> 1) * 32 + (warp == 11 ? 16 : 0) + (lane >> 1), qt = lane & 1;
        float sm = 0.f, sq = 0.f, shift = 0.f;
        int s = 0; uint32_t ph = 0;
#pragma unroll 1
        for (int kb = 0; kb < 8; kb++) {
          mbar_wait_idle(bar_full + 8 * s, ph);
          const uint32_t base = sbase + s * C::STAGE_BYTES + r * 128;
          if (kb == 0) { uint32_t f; asm volatile("ld.shared.u32 %0, [%1];" : "=r"(f) : "r"(base + ((r & 7) << 4))); shift = bf_lo(f); }
#pragma unroll
          for (int i = 0; i < 4; i++) {
            uint4 v;
            asm volatile("ld.shared.v4.u32 {%0, %1, %2, %3}, [%4];" : "=r"(v.x), "=r"(v.y), "=r"(v.z), "=r"(v.w) : "r"(base + (((qt * 4 + i) ^ (r & 7)) << 4)));
            float d;
            d = bf_lo(v.x) - shift; sm += d; sq = fmaf(d, d, sq); d = bf_hi(v.x) - shift; sm += d; sq = fmaf(d, d, sq);
            d = bf_lo(v.y) - shift; sm += d; sq = fmaf(d, d, sq); d = bf_hi(v.y) - shift; sm += d; sq = fmaf(d, d, sq);
            d = bf_lo(v.z) - shift; sm += d; sq = fmaf(d, d, sq); d = bf_hi(v.z) - shift; sm += d; sq = fmaf(d, d, sq);
            d = bf_lo(v.w) - shift; sm += d; sq = fmaf(d, d, sq); d = bf_hi(v.w) - shift; sm += d; sq = fmaf(d, d, sq);
          }
          __syncwarp();
          if (lane == 0) mbar_arrive(bar_empty + 8 * s);
          if (++s == C::STAGES) { s = 0; ph ^= 1; }
        }
        sm += __shfl_xor_sync(0xffffffffu, sm, 1); sq += __shfl_xor_sync(0xffffffffu, sq, 1);
        {
          const float md = sm * (1.f / 512);
          if (qt == 0) g_rowstat[((mt + nt) & 1) * S_LEN + mt * 256 + r] = make_float2(shift + md, fmaxf(sq - sm * md, 0.f));
        }
        __syncwarp();
        if (lane == 0) red_release_add(&g_cnt_row[mt * CNT_PAD], 1);
        spin_until(&g_cnt_col[nt * CNT_PAD], 8);
        __syncwarp();
        {
          const int col = (warp == 11 ? 96 : 0) + lane;
          const float* cp = &g_colpart[nt * 192 + col];
          float t[8][3];
#pragma unroll
          for (int k = 0; k < 8; k++)
#pragma unroll
            for (int i = 0; i < 3; i++) t[k][i] = __ldcg(cp + k * (3 * D_MOD) + i * 32);
#pragma unroll
          for (int i = 0; i < 3; i++) {
            const float a = ((t[0][i] + t[1][i]) + (t[2][i] + t[3][i])) + ((t[4][i] + t[5][i]) + (t[6][i] + t[7][i]));
            asm volatile("st.shared.f32 [%0], %1;" :: "r"(sbias + (col + i * 32) * 4), "f"(a) : "memory");
          }
        }

        __syncwarp();

        mbar_arrive(bar_res);
      } else if (warp == 10) {
        float cs[8];
#pragma unroll
        for (int e = 0; e < 8; e++) cs[e] = 0.f;
        int s = 0; uint32_t ph = 0;
        constexpr int NH4 = 4, NKB = 8;
        const uint32_t cbase = sbase + C::A_BYTES + (lane >> 3) * 8192 + (mt >> 1) * 16 * 128;
#pragma unroll 1
        for (int kb = 0; kb < NKB; kb++) {
          mbar_wait_idle(bar_full + 8 * s, ph);
          if (lane < 24) {
#pragma unroll
            for (int h = 0; h < NH4; h++) {
              uint4 v[4];
#pragma unroll
              for (int i = 0; i < 4; i++) {
                const int row = h * 4 + i;
                asm volatile("ld.shared.v4.u32 {%0, %1, %2, %3}, [%4];" : "=r"(v[i].x), "=r"(v[i].y), "=r"(v[i].z), "=r"(v[i].w)
                             : "r"(cbase + s * C::STAGE_BYTES + row * 128 + (((lane & 7) ^ (row & 7)) << 4)));
              }
#pragma unroll
              for (int i = 0; i < 4; i++) {
                cs[0] += bf_lo(v[i].x); cs[1] += bf_hi(v[i].x); cs[2] += bf_lo(v[i].y); cs[3] += bf_hi(v[i].y);
                cs[4] += bf_lo(v[i].z); cs[5] += bf_hi(v[i].z); cs[6] += bf_lo(v[i].w); cs[7] += bf_hi(v[i].w);
              }
            }
          }
          __syncwarp();
          if (CS > 1) { if (stgt >= 0) mbar_arrive_cluster(bar_empty + 8 * s, stgt); }
          else if (lane == 0) mbar_arrive(bar_empty + 8 * s);
          if (++s == C::STAGES) { s = 0; ph ^= 1; }
        }
        if (lane < 24) {
          float4* dst = reinterpret_cast<float4*>(&g_colpart[mt * (3 * D_MOD) + nt * 192 + lane * 8]);
          dst[0] = make_float4(cs[0], cs[1], cs[2], cs[3]); dst[1] = make_float4(cs[4], cs[5], cs[6], cs[7]);
        }
        __syncwarp();
        if (lane == 0) red_release_add(&g_cnt_col[nt * CNT_PAD], 1);
        if (lane == 0) { spin_until(&g_cnt_row[mt * CNT_PAD], 32); mbar_arrive(bar_res); }
      }
    }
    if (warp == 8 && lane == 0) {
      if constexpr (!EARLY) {
#pragma unroll 1
          for (int s = 0; s < NPRE; s++) { if (W_IS_A) loadA(s, s); else loadB(s, s); }
        if (C::EPI != EPI_QKV) pdl_wait();
#pragma unroll 1
        for (int s = 0; s < C::STAGES; s++) {
          if (FILLD < C::STAGES && s >= FILLD) mbar_wait(bar_full + 8 * (s - FILLD), 0);
          if (s >= NPRE) { if (W_IS_A) loadA(s, s); else loadB(s, s); }
          if (W_IS_A) loadB(s, s); else loadA(s, s);
        }
      } else if constexpr (FILL_QKV < C::STAGES) {
#pragma unroll 1
        for (int s = FILL_QKV; s < C::STAGES; s++) {
          mbar_wait(bar_full + 8 * (s - FILL_QKV), 0);
          mbar_expect_tx(bar_full + 8 * s, C::STAGE_BYTES);
          loadA(s, s); loadB(s, s);
        }
      }
      constexpr int RES_KB = C::EPI == EPI_OP ? OP_RES_KB : C::EPI == EPI_G2 ? G2_RES_KB : -1;
      auto loadRes = [&]() {
        mbar_expect_tx(bar_res, C::RES_BYTES);
        tma_load_2d(sres, &p.tmR, bar_res, nt * C::BN, mt * C::BM);
        tma_load_2d(sres + C::BM * 128, &p.tmR, bar_res, nt * C::BN + 64, mt * C::BM);
      };
      if (C::EPI == EPI_G2 || C::EPI == EPI_OP) { prefetch_tmap(&p.tmR); if (RES_KB < C::STAGES) loadRes(); }
      int s = 0; uint32_t ph = 0;
#pragma unroll 1
      for (int kb = C::STAGES; kb < C::KB; kb++) {
        mbar_wait(bar_empty + 8 * s, ph);
        mbar_expect_tx(bar_full + 8 * s, C::STAGE_BYTES);
        loadA(s, kb); loadB(s, kb);
        if ((C::EPI == EPI_G2 || C::EPI == EPI_OP) && kb == RES_KB) loadRes();
        if constexpr (C::EPI == EPI_OP) {
          if (kb >= 16 - OP_PF && kb < 16) l2_prefetch(reinterpret_cast<const char*>(p.w) + (size_t)blockIdx.x * (OP_PF * 4096) + (kb - (16 - OP_PF)) * 4096, 4096);
        }
        if constexpr (C::EPI == EPI_G1) {
          if (kb >= G1_PF0 && kb < G1_PF0 + G1_PF) l2_prefetch(reinterpret_cast<const char*>(p.w) + (size_t)blockIdx.x * (G1_PF * 4096) + (kb - G1_PF0) * 4096, 4096);
        }
        if (++s == C::STAGES) { s = 0; ph ^= 1; }
      }
    }
  } else {
    reg_alloc<C::CREG>();
    float acc[C::MREP][C::BN / 2];
    if constexpr (C::EPI == EPI_G1) {
      const uint32_t* bp = reinterpret_cast<const uint32_t*>(p.bias + nt * C::BN) + (lane & 3);
#pragma unroll
      for (int j = 0; j < C::BN / 8; j++) {
        const uint32_t b = __ldg(bp + 4 * j);
        acc[0][4 * j] = acc[0][4 * j + 2] = 0.5f * bf_lo(b); acc[0][4 * j + 1] = acc[0][4 * j + 3] = 0.5f * bf_hi(b);
      }
    } else {
#pragma unroll
      for (int m = 0; m < C::MREP; m++)
#pragma unroll
        for (int i = 0; i < C::BN / 2; i++) acc[m][i] = 0.f;
    }
    const int tw = threadIdx.x & 127;
    int tgt = -1;
    if (tw < C::CN) tgt = rm + tw * C::CM;
    else if (tw < C::CN + C::CM - 1) { int j = tw - C::CN; if (j >= rm) j++; tgt = rn * C::CM + j; }
    int s = 0, sprev = 0; uint32_t ph = 0;
    float2 mk0 = make_float2(0.f, 0.f), mk1 = mk0; unsigned short braw0 = 0, braw1 = 0;
    if constexpr (C::EPI == EPI_G2) {
      pdl_wait();
      const int row = mt * C::BM + wg * 64 + (warp & 3) * 16 + (lane >> 2);
      mk0 = __ldcg(&g_rowmk[row]); mk1 = __ldcg(&g_rowmk[row + 8]);
      braw0 = __ldg(reinterpret_cast<const unsigned short*>(p.bias) + row); braw1 = __ldg(reinterpret_cast<const unsigned short*>(p.bias) + row + 8);
    }
    constexpr int TAILKB = C::EPI == EPI_G1 ? G1_TAILKB : C::EPI == EPI_QKV ? QKV_TAIL : 0;
#pragma unroll 1
    for (int kb = 0; kb < C::KB - TAILKB; kb++) {
      mbar_wait(bar_full + 8 * s, ph);
      const uint32_t sa = sbase + s * C::STAGE_BYTES, sb = sa + C::A_BYTES;
#pragma unroll
      for (int m = 0; m < C::MREP; m++) fence_regs(acc[m]);
      wg_fence();
#pragma unroll
      for (int k = 0; k < 4; k++) {
        uint64_t db;
        if (C::B_MN) {
          const int sl = (k * 16) / C::B_RS, ro = (k * 16) % C::B_RS;
          db = make_desc(sb + sl * (C::B_BYTES / C::CM) + ro * C::B_RB, C::B_RS * C::B_RB, 8 * C::B_RB, C::B_RB == 128 ? 1 : 2);
        } else db = make_desc(sb + k * 32, 0, 1024, 1);
#pragma unroll
        for (int m = 0; m < C::MREP; m++) {
          uint64_t da; const int mb = wg * C::MREP + m;
          if (C::A_MN) {
            const int sl = (k * 16) / C::A_RS, ro = (k * 16) % C::A_RS;
            da = make_desc(sa + sl * (C::A_BYTES / C::CN) + mb * (C::A_RS * 128) + ro * 128, 0, 1024, 1);
          } else da = make_desc(sa + mb * 8192 + k * 32, 0, 1024, 1);
          WG<C::BN>::template mma<C::A_MN, C::B_MN>(acc[m], da, db, 1);
        }
      }
      wg_commit();
      if (kb > 0) {
        wg_wait<1>();
        if (CS > 1) { if (tgt >= 0) mbar_arrive_cluster(bar_empty + 8 * sprev, tgt); }
        else if (C::EPI == EPI_QKV) {
          if (tw == 0) asm volatile("mbarrier.arrive.shared::cta.b64 _, [%0], %1;" :: "r"(bar_empty + 8 * sprev), "r"((wg == 0 && kb > 8) ? 4 : 1) : "memory");
        }
        else if (tw == 0) mbar_arrive(bar_empty + 8 * sprev);
      }
      sprev = s;
      if (++s == C::STAGES) { s = 0; ph ^= 1; }
    }
    if constexpr (C::EPI == EPI_G1) {
      const int w4 = warp & 3;
      const int lrow = w4 * 16 + ((lane >> 3) & 1) * 8 + (lane & 7), lcol = lane >> 4;
      const uint32_t stg0 = sbase + (wg == 0 ? sprev : s) * C::STAGE_BYTES;
      if (wg == 1) { wg_wait<0>(); named_bar_arrive(4, 256); named_bar_sync(3, 256); }
#pragma unroll
      for (int t = 0; t < TAILKB; t++) {
        mbar_wait(bar_full + 8 * s, ph);
        const uint32_t sa = sbase + s * C::STAGE_BYTES;
        if (++s == C::STAGES) { s = 0; ph ^= 1; }
        wg_fence();
#pragma unroll
        for (int k = 0; k < 4; k++) {
          const int sl = (k * 16) / C::A_RS, ro = (k * 16) % C::A_RS, slb = (k * 16) / C::B_RS, rob = (k * 16) % C::B_RS;
          const uint64_t da = make_desc(sa + sl * (C::A_BYTES / C::CN) + wg * (C::A_RS * 128) + ro * 128, 0, 1024, 1);
          const uint32_t b0 = sa + C::A_BYTES + slb * (C::B_BYTES / C::CM) + rob * C::B_RB;
          WG<C::BN>::template mma<1, 1>(acc[0], da, make_desc(b0, C::B_RS * C::B_RB, 8 * C::B_RB, 2), 1);
        }
        wg_commit();
      }
      if (wg == 0) named_bar_arrive(3, 256);
      wg_wait<0>();
      fence_regs(acc[0]);
      if (wg == 0) { named_bar_arrive(5, 256); named_bar_sync(4, 256); } else named_bar_sync(5, 256);
      const int row0 = mt * C::BM + wg * 64 + w4 * 16;
      const int sw = (lrow >> 1) & 3;
#pragma unroll
      for (int sl = 0; sl < 7; sl++) {
        float v[16];
#pragma unroll
        for (int e = 0; e < 16; e++) {
          const float y = acc[0][sl * 16 + e];
          const float t = tanh_mufu(y * fmaf(y * y, 8.f * 0.035677408136300125f, 2.f * 0.7978845608028654f));
          v[e] = fmaf(y, t, y);
        }
#pragma unroll
        for (int jj = 0; jj < 4; jj += 2)
          stmatrix_x4(stg0 + sl * 4096 + lrow * 64 + (((jj + lcol) ^ sw) << 4),
                      pack_bf16(v[4 * jj], v[4 * jj + 1]), pack_bf16(v[4 * jj + 2], v[4 * jj + 3]),
                      pack_bf16(v[4 * jj + 4], v[4 * jj + 5]), pack_bf16(v[4 * jj + 6], v[4 * jj + 7]));
        if (sl == G1_SPLIT0 - 1 || sl == G1_SPLIT1 - 1 || sl == 6) {
          fence_proxy_async();
          __syncwarp();
          if (lane == 0) {
            const int lo = sl == G1_SPLIT0 - 1 ? 0 : sl == G1_SPLIT1 - 1 ? G1_SPLIT0 : G1_SPLIT1;
#pragma unroll
            for (int t = lo; t <= sl; t++) tma_store_2d(&p.tmC, stg0 + t * 4096 + w4 * 1024, nt * C::BN + t * 32, row0);
            tma_store_commit();
          }
        }
      }
      if (lane == 0) tma_store_wait_read();
      if (CS > 1) { cluster_arrive_relaxed(); cluster_wait(); }
      return;
    }
    uint32_t stgq = sbase + wg * C::MREP * 6 * 4096;
    if constexpr (C::EPI == EPI_QKV && TAILKB > 0) {
      stgq = sbase + (wg == 0 ? sprev : s) * C::STAGE_BYTES;
      if (wg == 1) { wg_wait<0>(); named_bar_arrive(4, 256); named_bar_sync(3, 256); }
#pragma unroll
      for (int t = 0; t < TAILKB; t++) {
        mbar_wait(bar_full + 8 * s, ph);
        const uint32_t sa = sbase + s * C::STAGE_BYTES, sb = sa + C::A_BYTES;
        if (++s == C::STAGES) { s = 0; ph ^= 1; }
        wg_fence();
#pragma unroll
        for (int k = 0; k < 4; k++) {
          const uint64_t db = make_desc(sb + k * 16 * C::B_RB, C::B_RS * C::B_RB, 8 * C::B_RB, 1);
#pragma unroll
          for (int m = 0; m < C::MREP; m++)
            WG<C::BN>::template mma<C::A_MN, C::B_MN>(acc[m], make_desc(sa + (wg * C::MREP + m) * 8192 + k * 32, 0, 1024, 1), db, 1);
        }
        wg_commit();
      }
      if (wg == 0) named_bar_arrive(3, 256);
    }
    float2 rs[C::MREP][2];
    if constexpr (C::EPI == EPI_QKV) {
      mbar_wait(bar_res, 0);
#pragma unroll
      for (int m = 0; m < C::MREP; m++) {
        const int r0 = mt * C::BM + (wg * C::MREP + m) * 64 + (warp & 3) * 16 + (lane >> 2);
#pragma unroll
        for (int h = 0; h < 2; h++) {
          const float2 a = __ldcg(&g_rowstat[r0 + 8 * h]), b = __ldcg(&g_rowstat[S_LEN + r0 + 8 * h]);
          const float d = a.x - b.x;
          rs[m][h] = make_float2(0.5f * (a.x + b.x), rsqrtf(fmaf(256.f * d, d, a.y + b.y) * (1.f / D_MOD) + LN_EPS));
        }
      }
    }
    wg_wait<0>();
#pragma unroll
    for (int m = 0; m < C::MREP; m++) fence_regs(acc[m]);

    const int w4 = warp & 3, g = lane >> 2, c = lane & 3;
    const int lrow = w4 * 16 + ((lane >> 3) & 1) * 8 + (lane & 7);
    const int lcol = lane >> 4;

    if constexpr (C::EPI == EPI_QKV) {
      if (TAILKB > 0) { if (wg == 0) { named_bar_arrive(5, 256); named_bar_sync(4, 256); } else named_bar_sync(5, 256); }
      else named_bar_sync(1, 256);
      const float2* scol = reinterpret_cast<const float2*>(smem_raw + (sbias - smem_u32(smem_raw)));
      float* statp = g_stats + nt * 6 * 128 + ((mt * C::BM + wg * C::MREP * 64) >> 4) + w4;
      const uint32_t stg0 = stgq + lrow * 64;
      const int lsw = (lrow >> 1) & 3;
      uint32_t myst = 0;
#pragma unroll
      for (int ch = 0; ch < 3; ch++) {
        float2 cs[8];
#pragma unroll
        for (int j = 0; j < 8; j++) cs[j] = scol[ch * 32 + j * 4 + c];
#pragma unroll
        for (int m = 0; m < C::MREP; m++) {
          const float2 rs0 = rs[m][0], rs1 = rs[m][1];
          const uint32_t stg = stg0 + (m * 3 + ch) * 8192;
#pragma unroll
          for (int hs = 0; hs < 2; hs++) {
            const int gs = nt * 6 + ch * 2 + hs;
            const float sc = gs < NH ? QSCALE : 1.f;
            const float a0 = rs0.y * sc, a1 = rs1.y * sc;
            float v[16];
#pragma unroll
            for (int j = 0; j < 4; j++) {
              const float2 cc = cs[hs * 4 + j];
              const float* a = &acc[m][(ch * 2 + hs) * 16 + 4 * j];
              v[4 * j + 0] = fmaf(-rs0.x, cc.x, a[0]) * a0; v[4 * j + 1] = fmaf(-rs0.x, cc.y, a[1]) * a0;
              v[4 * j + 2] = fmaf(-rs1.x, cc.x, a[2]) * a1; v[4 * j + 3] = fmaf(-rs1.x, cc.y, a[3]) * a1;
            }
#pragma unroll
            for (int jj = 0; jj < 4; jj += 2)
              stmatrix_x4(stg + hs * 4096 + (((jj + lcol) ^ lsw) << 4),
                          pack_bf16(v[4 * jj], v[4 * jj + 1]), pack_bf16(v[4 * jj + 2], v[4 * jj + 3]),
                          pack_bf16(v[4 * jj + 4], v[4 * jj + 5]), pack_bf16(v[4 * jj + 6], v[4 * jj + 7]));
            float s0 = v[0] * v[0], s1 = v[2] * v[2], s2 = v[1] * v[1], s3 = v[3] * v[3];
#pragma unroll
            for (int j = 1; j < 4; j++) {
              s0 = fmaf(v[4 * j], v[4 * j], s0); s2 = fmaf(v[4 * j + 1], v[4 * j + 1], s2);
              s1 = fmaf(v[4 * j + 2], v[4 * j + 2], s1); s3 = fmaf(v[4 * j + 3], v[4 * j + 3], s3);
            }
            s0 += s2; s1 += s3;
            s0 += __shfl_xor_sync(0xffffffffu, s0, 1); s1 += __shfl_xor_sync(0xffffffffu, s1, 1);
            s0 += __shfl_xor_sync(0xffffffffu, s0, 2); s1 += __shfl_xor_sync(0xffffffffu, s1, 2);
            uint32_t st = max(__float_as_uint(s0), __float_as_uint(s1));
            st = __reduce_max_sync(0xffffffffu, st);
            if (lane == (ch * 2 + hs) * 2 + m) myst = st;
          }
          fence_proxy_async();
          __syncwarp();
          if (lane == 0) {
            const uint32_t src0 = stgq + (m * 3 + ch) * 8192 + w4 * 1024;
            bf16* dst0 = g_qkv + ((size_t)(nt * 6 + ch * 2) * S_LEN + mt * C::BM + (wg * C::MREP + m) * 64 + w4 * 16) * DH;
            {
            bulk_store(dst0, src0, 1024);
            bulk_store(dst0 + (size_t)S_LEN * DH, src0 + 4096, 1024);
            }
            tma_store_commit();
          }
        }
      }
      if (lane < 12) statp[(lane >> 1) * 128 + (lane & 1) * 4] = __uint_as_float(myst);
      if (lane == 0) tma_store_wait_read();
    } else if constexpr (C::EPI == EPI_OP) {
      pdl_wait();
      mbar_wait(bar_res, 0);
      const int rr = wg * 64 + lrow;
      const int row = mt * C::BM + wg * 64 + w4 * 16 + g;
      float s0 = 0.f, s1 = 0.f, s2 = 0.f, s3 = 0.f;
#pragma unroll
      for (int j = 0; j < 16; j += 2) {
        const int jj = j + lcol;
        const uint32_t addr = sres + (jj >> 3) * (C::BM * 128) + rr * 128 + (((jj & 7) ^ (rr & 7)) << 4);
        uint32_t r0, r1, r2, r3;
        ldmatrix_x4(addr, r0, r1, r2, r3);
        float* a = &acc[0][4 * j];
        a[0] += bf_lo(r0); a[1] += bf_hi(r0); a[2] += bf_lo(r1); a[3] += bf_hi(r1);
        a[4] += bf_lo(r2); a[5] += bf_hi(r2); a[6] += bf_lo(r3); a[7] += bf_hi(r3);
        s0 += a[0] + a[1]; s2 += a[4] + a[5]; s1 += a[2] + a[3]; s3 += a[6] + a[7];
      }
      s0 += s2; s1 += s3;
      s0 += __shfl_xor_sync(0xffffffffu, s0, 1); s1 += __shfl_xor_sync(0xffffffffu, s1, 1);
      s0 += __shfl_xor_sync(0xffffffffu, s0, 2); s1 += __shfl_xor_sync(0xffffffffu, s1, 2);
      const float mu0 = s0 * (1.f / 128), mu1 = s1 * (1.f / 128);
      float q0 = 0.f, q1 = 0.f, q2 = 0.f, q3 = 0.f;
#pragma unroll
      for (int j = 0; j < 16; j++) {
        const float d0 = acc[0][4 * j] - mu0, d1 = acc[0][4 * j + 1] - mu0, d2 = acc[0][4 * j + 2] - mu1, d3 = acc[0][4 * j + 3] - mu1;
        q0 = fmaf(d0, d0, q0); q2 = fmaf(d1, d1, q2); q1 = fmaf(d2, d2, q1); q3 = fmaf(d3, d3, q3);
      }
      q0 += q2; q1 += q3;
      q0 += __shfl_xor_sync(0xffffffffu, q0, 1); q1 += __shfl_xor_sync(0xffffffffu, q1, 1);
      q0 += __shfl_xor_sync(0xffffffffu, q0, 2); q1 += __shfl_xor_sync(0xffffffffu, q1, 2);
      if (c < 2) {
        const float mu = c ? mu1 : mu0, q = c ? q1 : q0;

        st_relaxed_u64(&g_hpart[nt * S_LEN + row + 8 * c], ((unsigned long long)(__float_as_uint(q) | 0x80000000u) << 32) | __float_as_uint(mu));
      }
      float4 pa, pb;
      {
        unsigned long long w0, w1, w2, w3; uint32_t n = 0;
        do {
          w0 = ld_relaxed_u64(&g_hpart[(2 * c) * S_LEN + row]); w1 = ld_relaxed_u64(&g_hpart[(2 * c + 1) * S_LEN + row]);
          w2 = ld_relaxed_u64(&g_hpart[(2 * c) * S_LEN + row + 8]); w3 = ld_relaxed_u64(&g_hpart[(2 * c + 1) * S_LEN + row + 8]);
          if (++n > (1u << 22)) __trap();
        } while (w0 == HP_EMPTY || w1 == HP_EMPTY || w2 == HP_EMPTY || w3 == HP_EMPTY);
        pa = make_float4(__uint_as_float((uint32_t)w0), __uint_as_float((uint32_t)(w0 >> 32) & 0x7fffffffu), __uint_as_float((uint32_t)w1), __uint_as_float((uint32_t)(w1 >> 32) & 0x7fffffffu));
        pb = make_float4(__uint_as_float((uint32_t)w2), __uint_as_float((uint32_t)(w2 >> 32) & 0x7fffffffu), __uint_as_float((uint32_t)w3), __uint_as_float((uint32_t)(w3 >> 32) & 0x7fffffffu));
        __syncwarp();
      }
      float m0 = pa.x + pa.z, m1 = pb.x + pb.z;
      m0 += __shfl_xor_sync(0xffffffffu, m0, 1); m1 += __shfl_xor_sync(0xffffffffu, m1, 1);
      m0 += __shfl_xor_sync(0xffffffffu, m0, 2); m1 += __shfl_xor_sync(0xffffffffu, m1, 2);
      m0 *= 0.125f; m1 *= 0.125f;
      float v0 = pa.y + pa.w + 128.f * ((pa.x - m0) * (pa.x - m0) + (pa.z - m0) * (pa.z - m0));
      float v1 = pb.y + pb.w + 128.f * ((pb.x - m1) * (pb.x - m1) + (pb.z - m1) * (pb.z - m1));
      v0 += __shfl_xor_sync(0xffffffffu, v0, 1); v1 += __shfl_xor_sync(0xffffffffu, v1, 1);
      v0 += __shfl_xor_sync(0xffffffffu, v0, 2); v1 += __shfl_xor_sync(0xffffffffu, v1, 2);
      v0 *= (1.f / D_MOD); v1 *= (1.f / D_MOD);
      const float r10 = rsqrtf(v0 + LN_EPS), r11 = rsqrtf(v1 + LN_EPS);
      const float k0 = 0.5f * r10 * rsqrtf(v0 * r10 * r10 + LN_EPS), k1 = 0.5f * r11 * rsqrtf(v1 * r11 * r11 + LN_EPS);
#pragma unroll
      for (int hf = 0; hf < 2; hf++) {
#pragma unroll
        for (int j = hf * 8; j < hf * 8 + 8; j += 2) {
          const int jj = j + lcol;
          const uint32_t addr = sres + (jj >> 3) * (C::BM * 128) + rr * 128 + (((jj & 7) ^ (rr & 7)) << 4);
          const float* a = &acc[0][4 * j];
          stmatrix_x4(addr, pack_bf16((a[0] - m0) * k0, (a[1] - m0) * k0), pack_bf16((a[2] - m1) * k1, (a[3] - m1) * k1),
                            pack_bf16((a[4] - m0) * k0, (a[5] - m0) * k0), pack_bf16((a[6] - m1) * k1, (a[7] - m1) * k1));
        }
        fence_proxy_async();
        __syncwarp();
        if (lane == 0) {
          tma_store_2d(&p.tmC2, sres + hf * (C::BM * 128) + (wg * 64 + w4 * 16) * 128, nt * C::BN + hf * 64, mt * C::BM + wg * 64 + w4 * 16);
          tma_store_commit();
        }
      }
      if (nt == 0 && c < 2) g_rowmk[row + 8 * c] = c ? make_float2(m1, 1.f / k1) : make_float2(m0, 1.f / k0);
      if (lane == 0) tma_store_wait_read();
    } else {
      const float b0 = bf_lo(braw0) + mk0.x, b1 = bf_lo(braw1) + mk1.x, ik0 = mk0.y, ik1 = mk1.y;
      mbar_wait(bar_res, 0);
      const int rr = wg * 64 + lrow;
#pragma unroll
      for (int hf = 0; hf < 2; hf++) {
#pragma unroll
        for (int j = hf * 8; j < hf * 8 + 8; j += 2) {
          const int jj = j + lcol;
          const uint32_t addr = sres + (jj >> 3) * (C::BM * 128) + rr * 128 + (((jj & 7) ^ (rr & 7)) << 4);
          uint32_t r0, r1, r2, r3;
          ldmatrix_x4(addr, r0, r1, r2, r3);
          const float* a = &acc[0][4 * j];
          r0 = pack_bf16(fmaf(bf_lo(r0), ik0, a[0] + b0), fmaf(bf_hi(r0), ik0, a[1] + b0));
          r1 = pack_bf16(fmaf(bf_lo(r1), ik1, a[2] + b1), fmaf(bf_hi(r1), ik1, a[3] + b1));
          r2 = pack_bf16(fmaf(bf_lo(r2), ik0, a[4] + b0), fmaf(bf_hi(r2), ik0, a[5] + b0));
          r3 = pack_bf16(fmaf(bf_lo(r3), ik1, a[6] + b1), fmaf(bf_hi(r3), ik1, a[7] + b1));
          stmatrix_x4(addr, r0, r1, r2, r3);
        }
        fence_proxy_async();
        __syncwarp();
        if (lane == 0) {
          tma_store_2d(&p.tmC, sres + hf * (C::BM * 128) + (wg * 64 + w4 * 16) * 128, nt * C::BN + hf * 64, mt * C::BM + wg * 64 + w4 * 16);
          tma_store_commit();
        }
      }
      if (lane == 0) tma_store_wait_read();
    }
    if (CS > 1) { cluster_arrive_relaxed(); cluster_wait(); }
  }
}

#define QKV_CM 1
#define QKV_CN 1
#define QKV_CREG 232
#define QKV_PREG 40
typedef Cfg<EPI_QKV, 2, 192, 0, 1, 128, 4, QKV_CM, QKV_CN, 8, 16, 16, QKV_CREG, QKV_PREG> CfgQKV;
#define OP_CM 1
#define OP_CN 2
typedef Cfg<EPI_OP,  1, 128, 0, 1, 128, 6, OP_CM, OP_CN, 16, 8, 16, 232, 40> CfgOP;
#define G1_CM 2
#define G1_CN 1
#define G2_CM 1
#define G2_CN 2
typedef Cfg<EPI_G1,  1, 224, 1, 1, 64,  5, G1_CM, G1_CN, 8, 16, 32, 232, 40> CfgG1;
typedef Cfg<EPI_G2,  1, 128, 1, 0, 128, 6, G2_CM, G2_CN, 16, 8, 56, 232, 40> CfgG2;

constexpr int ATT_STAGES = 8;
constexpr int KV_STAGE = 16384;
constexpr int ATT_QBYTES = 512 * 64;
constexpr int ATT_SMEM = ATT_STAGES * KV_STAGE + ATT_QBYTES + 1024 + 256 + 1024;
constexpr int ATT_NCW = 4;
constexpr int ATT_THREADS = ATT_NCW * 128 + 128;

DEVINL uint32_t pin_ureg(uint32_t v) { uint32_t r; asm volatile("redux.sync.or.b32 %0, %1, 0xffffffff;" : "=r"(r) : "r"(v)); return r; }
DEVINL uint32_t pin_ureg2(uint32_t v) { uint32_t r; asm volatile("redux.sync.and.b32 %0, %1, 0xffffffff;" : "=r"(r) : "r"(v)); return r; }
DEVINL uint32_t ex2_pair(float x0, float x1) {
  const uint32_t y0 = __float_as_uint(x0 + 33150.0f);
  const uint32_t y1 = __float_as_uint(x1 + 33150.0f);
  uint32_t w, e, g, s;
  asm("prmt.b32 %0, %1, %2, 0x6420;" : "=r"(w) : "r"(y0), "r"(y1));
  asm("prmt.b32 %0, %1, %2, 0x5B1B;" : "=r"(e) : "r"(y0), "r"(y1));
  asm("mul.rn.f16x2 %0, %1, %2;" : "=r"(g) : "r"(w), "r"(0x56815681u));
  asm("fma.rn.f16x2 %0, %1, %1, %2;" : "=r"(s) : "r"(g), "r"(0x00560056u));
  return (e >> 1) + s;
}

#define PAIR_MASK 0x1F1F
__host__ __device__ constexpr bool use_pair(int i) { return ((PAIR_MASK >> i) & 1) != 0; }

DEVINL void att_qk_first(float (&d)[32], const uint32_t (&a)[4], uint64_t db) {
  asm volatile("wgmma.mma_async.sync.aligned.m64n64k16.f32.bf16.bf16 "
    "{%0, %1, %2, %3, %4, %5, %6, %7, %8, %9, %10, %11, %12, %13, %14, %15, %16, %17, %18, %19, %20, %21, %22, %23, %24, %25, %26, %27, %28, %29, %30, %31}, "
    "{%32, %33, %34, %35}, %36, 0, 1, 1, 0;\n"
    : "=f"(d[0]), "=f"(d[1]), "=f"(d[2]), "=f"(d[3]), "=f"(d[4]), "=f"(d[5]), "=f"(d[6]), "=f"(d[7]), "=f"(d[8]), "=f"(d[9]), "=f"(d[10]), "=f"(d[11]), "=f"(d[12]), "=f"(d[13]), "=f"(d[14]), "=f"(d[15]),
      "=f"(d[16]), "=f"(d[17]), "=f"(d[18]), "=f"(d[19]), "=f"(d[20]), "=f"(d[21]), "=f"(d[22]), "=f"(d[23]), "=f"(d[24]), "=f"(d[25]), "=f"(d[26]), "=f"(d[27]), "=f"(d[28]), "=f"(d[29]), "=f"(d[30]), "=f"(d[31])
    : "r"(a[0]), "r"(a[1]), "r"(a[2]), "r"(a[3]), "l"(db));
}
DEVINL void att_qk_acc(float (&d)[32], const uint32_t (&a)[4], uint64_t db) {
  asm volatile("wgmma.mma_async.sync.aligned.m64n64k16.f32.bf16.bf16 "
    "{%0, %1, %2, %3, %4, %5, %6, %7, %8, %9, %10, %11, %12, %13, %14, %15, %16, %17, %18, %19, %20, %21, %22, %23, %24, %25, %26, %27, %28, %29, %30, %31}, "
    "{%32, %33, %34, %35}, %36, 1, 1, 1, 0;\n"
    : "+f"(d[0]), "+f"(d[1]), "+f"(d[2]), "+f"(d[3]), "+f"(d[4]), "+f"(d[5]), "+f"(d[6]), "+f"(d[7]), "+f"(d[8]), "+f"(d[9]), "+f"(d[10]), "+f"(d[11]), "+f"(d[12]), "+f"(d[13]), "+f"(d[14]), "+f"(d[15]),
      "+f"(d[16]), "+f"(d[17]), "+f"(d[18]), "+f"(d[19]), "+f"(d[20]), "+f"(d[21]), "+f"(d[22]), "+f"(d[23]), "+f"(d[24]), "+f"(d[25]), "+f"(d[26]), "+f"(d[27]), "+f"(d[28]), "+f"(d[29]), "+f"(d[30]), "+f"(d[31])
    : "r"(a[0]), "r"(a[1]), "r"(a[2]), "r"(a[3]), "l"(db));
}
DEVINL void att_pv(float (&d)[20], uint32_t a0, uint32_t a1, uint32_t a2, uint32_t a3, uint64_t db) {
  asm volatile("wgmma.mma_async.sync.aligned.m64n40k16.f32.bf16.bf16 "
    "{%0, %1, %2, %3, %4, %5, %6, %7, %8, %9, %10, %11, %12, %13, %14, %15, %16, %17, %18, %19}, "
    "{%20, %21, %22, %23}, %24, 1, 1, 1, 1;\n"
    : "+f"(d[0]), "+f"(d[1]), "+f"(d[2]), "+f"(d[3]), "+f"(d[4]), "+f"(d[5]), "+f"(d[6]), "+f"(d[7]), "+f"(d[8]), "+f"(d[9]), "+f"(d[10]), "+f"(d[11]), "+f"(d[12]), "+f"(d[13]), "+f"(d[14]), "+f"(d[15]),
      "+f"(d[16]), "+f"(d[17]), "+f"(d[18]), "+f"(d[19])
    : "r"(a0), "r"(a1), "r"(a2), "r"(a3), "l"(db));
}
DEVINL void mbar_wait_fast(uint32_t bar, uint32_t parity) {
  asm volatile("{\n.reg .pred P1;\n.reg .pred P2;\n.reg .u32 cnt;\n"
    "mbarrier.try_wait.parity.shared::cta.b64 P1, [%0], %1;\n"
    "@P1 bra.uni DONE;\n"
    "mov.u32 cnt, 0;\n"
    "LAB_WAIT:\n"
    "mbarrier.try_wait.parity.shared::cta.b64 P1, [%0], %1;\n"
    "@P1 bra.uni DONE;\n"
    "add.u32 cnt, cnt, 1;\n"
    "setp.lt.u32 P2, cnt, 4194304;\n"
    "@P2 bra.uni LAB_WAIT;\n"
    "trap;\n"
    "DONE:\n}" :: "r"(bar), "r"(parity) : "memory");
}

struct alignas(64) AttnParams { CUtensorMap tmKV; const bf16* wo; const bf16* w1; };

__global__ void __launch_bounds__(ATT_THREADS, 1) attn_kernel(const __grid_constant__ AttnParams p) {
  extern __shared__ uint8_t smem_raw[];
  const uint32_t sbase = (smem_u32(smem_raw) + 1023) & ~1023u;
  const uint32_t sq = sbase + ATT_STAGES * KV_STAGE;
  const uint32_t ones = sq + ATT_QBYTES;
  const uint32_t bar_full = ones + 1024, bar_empty = bar_full + 8 * ATT_STAGES, bar_q = bar_empty + 8 * ATT_STAGES;
  const int warp = threadIdx.x >> 5, lane = threadIdx.x & 31, wg = threadIdx.x >> 7;
  const int head = blockIdx.x >> 2, qb = blockIdx.x & 3;
  constexpr int NITEMS = 512 / (ATT_NCW * 64);
  constexpr int NT = S_LEN / 128;
  if (warp == ATT_NCW * 4) {
    if (lane < 2 * ATT_STAGES + 2) mbar_init(bar_full + 8 * lane, (lane >= ATT_STAGES && lane < 2 * ATT_STAGES) ? ATT_NCW : 1);
    if (lane >= 2 * ATT_STAGES && lane < 2 * ATT_STAGES + 2) mbar_expect_tx(bar_full + 8 * lane, ATT_QBYTES / 2);
    fence_barrier_init();
  }
  if (threadIdx.x < 64) {
    asm volatile("st.shared.v4.u32 [%0], {%1, %2, %2, %2};" :: "r"(ones + threadIdx.x * 16), "r"(0x00003F80u), "r"(0u) : "memory");
    fence_proxy_async();
  }
  __syncthreads();
  pdl_launch();

  if (wg == ATT_NCW) {
    reg_dealloc<ATT_PREG>();
    if (warp == ATT_NCW * 4 && lane == 0) {
      pdl_wait();
      int s = 0; uint32_t ph = 1;
#pragma unroll 1
      for (int it = 0; it < NITEMS * NT; it++) {
        const int j = it % NT;
        mbar_wait_idle(bar_empty + 8 * s, ph);
        if (ATT_FILL < ATT_STAGES && it >= ATT_FILL && it < ATT_STAGES) mbar_wait(bar_full + 8 * (it - ATT_FILL), 0);
        const uint32_t fb = bar_full + 8 * s, dst = sbase + s * KV_STAGE;
        mbar_expect_tx(fb, KV_STAGE);
        bulk_load(dst, g_qkv + ((size_t)(NH + head) * S_LEN + j * 128) * DH, 8192, fb);
        if (it == 0) bulk_load(sq, g_qkv + ((size_t)head * S_LEN + qb * 512) * DH, 16384, bar_q);
        bulk_load(dst + 8192, g_qkv + ((size_t)(2 * NH + head) * S_LEN + j * 128) * DH, 8192, fb);
        if (it == ATT_Q2) bulk_load(sq + 16384, g_qkv + ((size_t)head * S_LEN + qb * 512 + 256) * DH, 16384, bar_q + 8);
        if (it >= ATT_WO && it < ATT_WO + 2) l2_prefetch(reinterpret_cast<const char*>(p.wo) + (size_t)blockIdx.x * (D_MOD * D_MOD * 2 / 128) + (it - ATT_WO) * 8192, 8192);
        if (++s == ATT_STAGES) { s = 0; ph ^= 1; }
      }
    }
  } else {
    reg_alloc<ATT_CREG>();
    pdl_wait();
    if (blockIdx.x == 0 && threadIdx.x < 16) { g_cnt_col[threadIdx.x * CNT_PAD] = 0; if (threadIdx.x < 8) g_cnt_row[threadIdx.x * CNT_PAD] = 0; }
    const int w4 = warp & 3, g = lane >> 2, c = lane & 3;
    const uint64_t kdesc0 = make_desc(sbase, 16, 512, 2);
    const uint32_t vlo0 = ((sbase + 8192) >> 4) | (((ones - (sbase + 8192)) >> 4) << 16);
    const uint64_t vhi = ((uint64_t)(512 >> 4) << 32) | ((uint64_t)2 << 62);
    const int tw = threadIdx.x & 127;
    uint32_t kb = 0, vb = 0;
#pragma unroll
    for (int i = 0; i < 4; i++) {
      kb = max(kb, __float_as_uint(g_stats[(NH + head) * 128 + lane + 32 * i]));
      vb = max(vb, __float_as_uint(g_stats[(2 * NH + head) * 128 + lane + 32 * i]));
    }
    uint32_t qbits[NITEMS];
#pragma unroll
    for (int it = 0; it < NITEMS; it++) qbits[it] = __float_as_uint(g_stats[head * 128 + ((qb * 512 + it * (ATT_NCW * 64) + wg * 64) >> 4) + (lane & 3)]);
    const float kmax = __uint_as_float(redux_max_u32(kb)), vmax = __uint_as_float(redux_max_u32(vb));
    uint32_t fastmask = 0;
#pragma unroll
    for (int it = 0; it < NITEMS; it++) {
      const float qmax = __uint_as_float(redux_max_u32(qbits[it]));
      if ((qmax * kmax <= 88.f * 88.f) && (vmax <= 9.0e14f) && (vmax >= 3.2e-5f)) fastmask |= 1u << it;
    }

    int st = 0; uint32_t ph = 0;
#pragma unroll 1
    for (int it = 0; it < NITEMS; it++) {
      const int row0 = qb * 512 + it * (ATT_NCW * 64) + wg * 64;
      uint32_t q[2][4];
      {
        mbar_wait(bar_q + 8 * it, 0);
        const int r = it * (ATT_NCW * 64) + wg * 64 + w4 * 16 + ((lane >> 3) & 1) * 8 + (lane & 7);
#pragma unroll
        for (int ks = 0; ks < 2; ks++)
          ldmatrix_x4(sq + r * 64 + (((ks * 2 + (lane >> 4)) ^ ((r >> 1) & 3)) << 4), q[ks][0], q[ks][1], q[ks][2], q[ks][3]);
      }
      const bool fast = (fastmask >> it) & 1;

      float o[20];
#pragma unroll
      for (int i = 0; i < 20; i++) o[i] = 0.f;
      fence_regs(o);
      float sa[32];
      uint32_t pa[16];
#define QK(S, st, half) do { \
        const uint64_t kd = kdesc0 + (uint64_t)((st) * (KV_STAGE >> 4) + (half) * 256); \
        wgmma_n64_rsz<0>(S, q[0][0], q[0][1], q[0][2], q[0][3], kd, 0); \
        wgmma_n64_rs<0>(S, q[1][0], q[1][1], q[1][2], q[1][3], kd + 2, 1); \
      } while (0)
#define PV(P, st, half) do { \
        const uint32_t vo = (st) * (KV_STAGE >> 4) + (half) * 256; \
        _Pragma("unroll") for (int kk = 0; kk < 4; kk++) { \
          const uint32_t off = vo + kk * 64; \
          const uint64_t vd = vhi | (uint64_t)(vlo0 + off - (off << 16)); \
          wgmma_n40_rs<1>(o, P[4 * kk], P[4 * kk + 1], P[4 * kk + 2], P[4 * kk + 3], vd, 1); \
        } \
      } while (0)
      mbar_wait(bar_full + 8 * st, ph);
      if (fast) {
#define VD64(off) ((uint64_t)(int64_t)((int)(off) * (1 - 65536)))
#define QK3(kd) do { att_qk_first(sa, q[0], (kd)); att_qk_acc(sa, q[1], (kd) + 2); } while (0)
        const uint64_t vdesc0 = vhi | vlo0;
        const uint64_t kbase = ((uint64_t)pin_ureg((uint32_t)(kdesc0 >> 32) + (qbits[0] >> 31)) << 32) | (uint32_t)kdesc0;
        const uint64_t vbase = ((uint64_t)pin_ureg2((uint32_t)(vdesc0 >> 32) + (qbits[0] >> 31)) << 32) | (uint32_t)vdesc0;
#define EXP_RANGE(lo, hi) do { \
          _Pragma("unroll") for (int i = (lo); i < (hi); i++) \
            pa[i] = use_pair(i) ? ex2_pair(sa[2 * i], sa[2 * i + 1]) : pack_bf16(ex2_mufu(sa[2 * i]), ex2_mufu(sa[2 * i + 1])); \
          _Pragma("unroll") for (int i = (lo); i < (hi); i++) asm volatile("" : "+r"(pa[i]) :: "memory"); \
        } while (0)
#define PVR(vd, lo, hi) do { _Pragma("unroll") for (int kk = (lo); kk < (hi); kk++) att_pv(o, pa[4 * kk], pa[4 * kk + 1], pa[4 * kk + 2], pa[4 * kk + 3], (vd) + VD64(kk * 64)); } while (0)
#define MMA_BATCH(kdn, vdc) do { wg_fence(); QK3(kdn); PVR(vdc, 0, PV_SPLIT); wg_commit(); PVR(vdc, PV_SPLIT, 4); wg_commit(); wg_wait<1>(); fence_regs(sa); } while (0)
        wg_fence(); QK3(kbase); wg_commit();
        wg_wait<0>(); fence_regs(sa);
#pragma unroll 1
        for (int j = NT / ATT_STAGES - 1; j >= 0; j--) {
#pragma unroll
          for (int t = 0; t < ATT_STAGES; t++) {
            EXP_RANGE(0, 4 * PV_SPLIT);
            wg_wait<0>();
            if (tw == 0 && (t > 0 || j < NT / ATT_STAGES - 1)) mbar_arrive(bar_empty + 8 * ((t + ATT_STAGES - 1) % ATT_STAGES));
            EXP_RANGE(4 * PV_SPLIT, 16);
            MMA_BATCH(kbase + t * 1024 + 256, vbase + VD64(t * 1024));
            EXP_RANGE(0, 4 * PV_SPLIT);
            if (t + 1 < ATT_STAGES) mbar_wait_fast(bar_full + 8 * (t + 1), ph);
            else { ph ^= 1; if (j > 0) mbar_wait_fast(bar_full, ph); }
            wg_wait<0>();
            EXP_RANGE(4 * PV_SPLIT, 16);
            MMA_BATCH(kbase + ((t + 1) % ATT_STAGES) * 1024, vbase + VD64(t * 1024 + 256));
          }
        }
        wg_wait<0>();
        if (tw == 0) mbar_arrive(bar_empty + 8 * (ATT_STAGES - 1));
      } else {
        float m0 = -INFINITY, m1 = -INFINITY;
#pragma unroll 1
        for (int u = 0; u < 2 * NT; u++) {
          const int half = u & 1;
          if (half == 0 && u > 0) mbar_wait(bar_full + 8 * st, ph);
          wg_fence(); QK(sa, st, half); wg_commit();
          wg_wait<0>(); fence_regs(sa);
          float x0 = m0, x1 = m1;
#pragma unroll
          for (int j = 0; j < 8; j++) {
            x0 = fmaxf(x0, fmaxf(sa[4 * j], sa[4 * j + 1]));
            x1 = fmaxf(x1, fmaxf(sa[4 * j + 2], sa[4 * j + 3]));
          }
          x0 = fmaxf(x0, __shfl_xor_sync(0xffffffffu, x0, 1)); x1 = fmaxf(x1, __shfl_xor_sync(0xffffffffu, x1, 1));
          x0 = fmaxf(x0, __shfl_xor_sync(0xffffffffu, x0, 2)); x1 = fmaxf(x1, __shfl_xor_sync(0xffffffffu, x1, 2));
          const float a0 = ex2_mufu(m0 - x0), a1 = ex2_mufu(m1 - x1);
          m0 = x0; m1 = x1;
#pragma unroll
          for (int j = 0; j < 5; j++) { o[4 * j] *= a0; o[4 * j + 1] *= a0; o[4 * j + 2] *= a1; o[4 * j + 3] *= a1; }
#pragma unroll
          for (int j = 0; j < 8; j++) {
            pa[2 * j] = pack_bf16(ex2_mufu(sa[4 * j] - x0), ex2_mufu(sa[4 * j + 1] - x0));
            pa[2 * j + 1] = pack_bf16(ex2_mufu(sa[4 * j + 2] - x1), ex2_mufu(sa[4 * j + 3] - x1));
          }
          fence_u32(pa); fence_regs(o);
          wg_fence(); PV(pa, st, half); wg_commit();
          wg_wait<0>(); fence_regs(o);
          if (half == 1) {
            if (tw == 0) mbar_arrive(bar_empty + 8 * st);
            if (++st == ATT_STAGES) { st = 0; ph ^= 1; }
          }
        }
      }
      fence_regs(o);
      const float l0 = __shfl_sync(0xffffffffu, o[16], lane & ~3);
      const float l1 = __shfl_sync(0xffffffffu, o[18], lane & ~3);
      const float r0 = 1.f / l0, r1 = 1.f / l1;
#pragma unroll
      for (int h = 0; h < 2; h++) {
        const float r = h ? r1 : r0;
        uint32_t v[4];
#pragma unroll
        for (int jj = 0; jj < 4; jj++) v[jj] = pack_bf16(o[4 * jj + 2 * h] * r, o[4 * jj + 2 * h + 1] * r);
        const bool b0 = c & 1, b1 = c & 2;
        uint32_t s0 = __shfl_xor_sync(0xffffffffu, b0 ? v[0] : v[1], 1), s1 = __shfl_xor_sync(0xffffffffu, b0 ? v[2] : v[3], 1);
        const uint32_t a0 = b0 ? s0 : v[0], a1 = b0 ? v[1] : s0, a2 = b0 ? s1 : v[2], a3 = b0 ? v[3] : s1;
        const uint32_t t0 = __shfl_xor_sync(0xffffffffu, b1 ? a0 : a2, 2), t1 = __shfl_xor_sync(0xffffffffu, b1 ? a1 : a3, 2);
        const uint4 w = b1 ? make_uint4(t0, t1, a2, a3) : make_uint4(a0, a1, t0, t1);
        *reinterpret_cast<uint4*>(g_o + (size_t)(row0 + w4 * 16 + g + 8 * h) * D_MOD + head * DH + 8 * c) = w;
      }
    }
    if (threadIdx.x < 64) reinterpret_cast<uint4*>(g_hpart)[blockIdx.x * 64 + threadIdx.x] = make_uint4(0u, 0u, 0u, 0u);
  }
}

typedef CUresult (*EncodeTiledFn)(CUtensorMap*, CUtensorMapDataType, cuuint32_t, void*, const cuuint64_t*, const cuuint64_t*, const cuuint32_t*,
                                  const cuuint32_t*, CUtensorMapInterleave, CUtensorMapSwizzle, CUtensorMapL2promotion, CUtensorMapFloatOOBfill);
static EncodeTiledFn g_encode = nullptr;

static CUtensorMap make_tmap(const void* base, int rank, const uint64_t* dims, const uint64_t* strides_bytes, const uint32_t* box, int swizzle_bytes) {
  CUtensorMap m;
  cuuint64_t gd[5]; cuuint64_t gs[5]; cuuint32_t bx[5]; cuuint32_t es[5];
  for (int i = 0; i < rank; i++) { gd[i] = dims[i]; bx[i] = box[i]; es[i] = 1; }
  for (int i = 0; i < rank - 1; i++) gs[i] = strides_bytes[i];
  CUtensorMapSwizzle sw = swizzle_bytes == 128 ? CU_TENSOR_MAP_SWIZZLE_128B : CU_TENSOR_MAP_SWIZZLE_64B;
  CUresult r = g_encode(&m, CU_TENSOR_MAP_DATA_TYPE_BFLOAT16, rank, (void*)base, gd, gs, bx, es, CU_TENSOR_MAP_INTERLEAVE_NONE, sw,
                        CU_TENSOR_MAP_L2_PROMOTION_L2_256B, CU_TENSOR_MAP_FLOAT_OOB_FILL_NONE);
  if (r != CUDA_SUCCESS) fprintf(stderr, "cuTensorMapEncodeTiled failed: %d\n", (int)r);
  return m;
}
static CUtensorMap tmap_2d(const void* base, uint64_t rows, uint64_t cols, uint32_t br, uint32_t bc, int swz) {
  uint64_t d[2] = {cols, rows}; uint64_t st[1] = {cols * 2}; uint32_t bx[2] = {bc, br};
  return make_tmap(base, 2, d, st, bx, swz);
}
static CUtensorMap tmap_mn(const void* base, uint64_t K, uint64_t MN, uint32_t row_bytes, uint32_t krows, uint32_t nchunks) {
  const uint32_t ce = row_bytes / 2;
  uint64_t d[3] = {ce, K, MN / ce}; uint64_t st[2] = {MN * 2, row_bytes}; uint32_t bx[3] = {ce, krows, nchunks};
  return make_tmap(base, 3, d, st, bx, row_bytes);
}

template<typename... KArgs, typename... Args>
static void launch(void (*kern)(KArgs...), int grid, int block, int smem, int cluster, bool pdl, Args... args) {
  cudaLaunchConfig_t cfg = {};
  cfg.gridDim = dim3(grid); cfg.blockDim = dim3(block); cfg.dynamicSmemBytes = smem; cfg.stream = cudaStreamPerThread;
  cudaLaunchAttribute at[2]; int n = 0;
  if (cluster > 1) { at[n].id = cudaLaunchAttributeClusterDimension; at[n].val.clusterDim.x = cluster; at[n].val.clusterDim.y = 1; at[n].val.clusterDim.z = 1; n++; }
  if (pdl) { at[n].id = cudaLaunchAttributeProgrammaticStreamSerialization; at[n].val.programmaticStreamSerializationAllowed = 1; n++; }
  cfg.attrs = at; cfg.numAttrs = n;
  cudaError_t e = cudaLaunchKernelEx(&cfg, kern, args...);
  if (e != cudaSuccess) fprintf(stderr, "launch failed: %s\n", cudaGetErrorString(e));
}


extern "C" void kernel_launch(void* const* d_in, const int* in_sizes, int n_in, void* d_out, int out_size) {
  const bf16* x    = (const bf16*)d_in[0];
  const bf16* wqkv = (const bf16*)d_in[1];
  const bf16* wo   = (const bf16*)d_in[2];
  const bf16* w1   = (const bf16*)d_in[4];
  const bf16* b1   = (const bf16*)d_in[5];
  const bf16* w2   = (const bf16*)d_in[6];
  const bf16* b2   = (const bf16*)d_in[7];
  bf16* out = (bf16*)d_out;

  static bool init = false;
  static bf16 *qkv, *o, *hn, *u;
  if (!init) {
    void* fn = nullptr; cudaDriverEntryPointQueryResult qr;
    cudaGetDriverEntryPoint("cuTensorMapEncodeTiled", &fn, cudaEnableDefault, &qr);
    g_encode = (EncodeTiledFn)fn;
    cudaGetSymbolAddress((void**)&qkv, g_qkv); cudaGetSymbolAddress((void**)&o, g_o);
    cudaGetSymbolAddress((void**)&hn, g_hn); cudaGetSymbolAddress((void**)&u, g_u);
    cudaFuncSetAttribute(gemm_kernel<CfgQKV>, cudaFuncAttributeMaxDynamicSharedMemorySize, CfgQKV::SMEM);
    cudaFuncSetAttribute(gemm_kernel<CfgOP>, cudaFuncAttributeMaxDynamicSharedMemorySize, CfgOP::SMEM);
    cudaFuncSetAttribute(gemm_kernel<CfgG1>, cudaFuncAttributeMaxDynamicSharedMemorySize, CfgG1::SMEM);
    cudaFuncSetAttribute(gemm_kernel<CfgG2>, cudaFuncAttributeMaxDynamicSharedMemorySize, CfgG2::SMEM);
    cudaFuncSetAttribute(attn_kernel, cudaFuncAttributeMaxDynamicSharedMemorySize, ATT_SMEM);
    init = true;
  }
  GemmParams pq, po, p1, p2; AttnParams pa;
  pq.tmA = tmap_2d(x, S_LEN, D_MOD, CfgQKV::BM / CfgQKV::CN, 64, 128);
  pq.tmB = tmap_mn(wqkv, D_MOD, 3 * D_MOD, 128, CfgQKV::B_RS, CfgQKV::B_CH);
  pq.tmC = tmap_2d(qkv, S_LEN, 3 * D_MOD, 16, 64, 128);
  pq.tmR = pq.tmC; pq.tmC2 = pq.tmC; pq.bias = nullptr; pq.x = x; pq.w = wqkv;
  pa.tmKV = tmap_2d(qkv, S_LEN, 3 * D_MOD, 128, 32, 64); pa.wo = wo; pa.w1 = w1;
  po.tmA = tmap_2d(o, S_LEN, D_MOD, CfgOP::BM / CfgOP::CN, 64, 128);
  po.tmB = tmap_mn(wo, D_MOD, D_MOD, 128, CfgOP::B_RS, CfgOP::B_CH);
  po.tmR = tmap_2d(x, S_LEN, D_MOD, 128, 64, 128); po.bias = nullptr; po.x = nullptr; po.w = w1;
  po.tmC2 = tmap_2d(hn, S_LEN, D_MOD, 16, 64, 128); po.tmC = po.tmC2;
  p1.tmA = tmap_mn(hn, S_LEN, D_MOD, 128, CfgG1::A_RS, CfgG1::A_CH);
  p1.tmB = tmap_mn(w1, S_LEN, F_DIM, 64, CfgG1::B_RS, CfgG1::B_CH);
  p1.tmC = tmap_2d(u, D_MOD, F_DIM, 16, 32, 64);
  p1.tmR = p1.tmC; p1.tmC2 = p1.tmC; p1.bias = b1; p1.x = nullptr; p1.w = w2;
  p2.tmA = tmap_mn(w2, F_DIM, S_LEN, 128, CfgG2::A_RS, CfgG2::A_CH);
  p2.tmB = tmap_2d(u, D_MOD, F_DIM, CfgG2::BN / CfgG2::CM, 64, 128);
  p2.tmC = tmap_2d(out, S_LEN, D_MOD, 16, 64, 128);
  p2.tmR = tmap_2d(hn, S_LEN, D_MOD, 128, 64, 128); p2.tmC2 = p2.tmC; p2.bias = b2; p2.x = nullptr; p2.w = nullptr;

  const bool pdl = true;
  launch(gemm_kernel<CfgQKV>, CfgQKV::GRID, 384, CfgQKV::SMEM, CfgQKV::CM * CfgQKV::CN, false, pq);
  launch(attn_kernel, 128, ATT_THREADS, ATT_SMEM, 1, pdl, pa);
  launch(gemm_kernel<CfgOP>, CfgOP::GRID, 384, CfgOP::SMEM, CfgOP::CM * CfgOP::CN, pdl, po);
  launch(gemm_kernel<CfgG1>, CfgG1::GRID, 384, CfgG1::SMEM, CfgG1::CM * CfgG1::CN, pdl, p1);
  launch(gemm_kernel<CfgG2>, CfgG2::GRID, 384, CfgG2::SMEM, CfgG2::CM * CfgG2::CN, pdl, p2);
}
```
